```python
import torch

def _softmax(x, axis=-1):
    return torch.softmax(x, dim=axis)

def _gelu(x):
    return torch.nn.functional.gelu(x, approximate='tanh')

def _silu(x):
    return torch.nn.functional.silu(x)

def _sigmoid(x):
    return torch.sigmoid(x)

def _layernorm(x, axis=-1, eps=1e-05):
    m = x.mean(dim=axis, keepdim=True)
    v = x.var(dim=axis, keepdim=True, unbiased=False)
    return (x - m) / torch.sqrt(v + eps)

def _scatter_add(tgt, idx, src, axis=0):
    return tgt.clone().index_add_(axis, idx, src)

def _segment_sum(src, seg, n):
    out = torch.zeros((n,) + src.shape[1:], dtype=src.dtype)
    return out.index_add_(0, seg, src)

def _pad(x, pw):
    flat = tuple((v for pair in reversed(pw) for v in pair))
    return torch.nn.functional.pad(x, flat)
kernel_name = 'standalone__tree_speculative_verify_tree_attention_over_candidate_token_tree__sampling'

def setup_inputs():

    _w = lambda a: (lambda t: t.to(torch.bfloat16) if t.is_floating_point() else t)(torch.as_tensor(a))
    B, Hq, Hkv, T, C, D = (16, 32, 8, 32, 4096, 128)
    tree_mask = torch.zeros((B, T, T), dtype=float)
    for b in range(B):
        parent = torch.zeros(T, dtype=torch.int64)
        for i in range(1, T):
            parent[i] = int(torch.randint(0, i, (1,)).item())
        for i in range(T):
            j = i
            tree_mask[b, i, j] = 1.0
            while j > 0:
                j = parent[j]
                tree_mask[b, i, j] = 1.0
    return {'q': _w((lambda *s: torch.randn(*s, dtype=torch.bfloat16) * 0.8)(B, Hq, T, D)), 'k_cache': _w((lambda *s: torch.randn(*s, dtype=torch.bfloat16) * 0.8)(B, Hkv, C, D)), 'v_cache': _w((lambda *s: torch.randn(*s, dtype=torch.bfloat16) * 0.05)(B, Hkv, C, D)), 'k_tree': _w((lambda *s: torch.randn(*s, dtype=torch.bfloat16) * 0.8)(B, Hkv, T, D)), 'v_tree': _w((lambda *s: torch.randn(*s, dtype=torch.bfloat16) * 0.05)(B, Hkv, T, D)), 'tree_mask': _w(tree_mask)}

def reference(q, k_cache, v_cache, k_tree, v_tree, tree_mask):
    B, Hq, T, D = q.shape
    Hkv, C = (k_cache.shape[1], k_cache.shape[2])
    rep = Hq // Hkv
    kc = (lambda x, n, axis: torch.repeat_interleave(x, n, dim=axis))(k_cache, rep, axis=1)
    vc = (lambda x, n, axis: torch.repeat_interleave(x, n, dim=axis))(v_cache, rep, axis=1)
    kt = (lambda x, n, axis: torch.repeat_interleave(x, n, dim=axis))(k_tree, rep, axis=1)
    vt = (lambda x, n, axis: torch.repeat_interleave(x, n, dim=axis))(v_tree, rep, axis=1)
    k = torch.concatenate([kc, kt], axis=2)
    v = torch.concatenate([vc, vt], axis=2)
    scale = D ** (-0.5)
    scores = torch.einsum('bhqd,bhkd->bhqk', q, k) * scale
    ctx_mask = torch.ones((B, 1, T, C), dtype=scores.dtype)
    tm = tree_mask[:, None, :, :].clone()
    full_mask = torch.concatenate([ctx_mask, tm], axis=-1)
    scores = scores + (1.0 - full_mask) * -1000000000.0
    p = _softmax(scores, axis=-1)
    return torch.einsum('bhqk,bhkd->bhqd', p, v)
```

```cpp
#include <cuda_runtime.h>
#include <cuda_bf16.h>
#include <cuda.h>
#include <stddef.h>
#include <stdint.h>

namespace {

constexpr int kB = 16, kHq = 32, kHkv = 8, kT = 32, kC = 4096, kD = 128;
constexpr int kCtas = kB * kHkv;
constexpr int kRows = (kHq / kHkv) * kT;
constexpr int kTile = 128;
constexpr int kTiles = kC / kTile;
constexpr int kItems = 2 * kTiles;
constexpr int kTileBytes = kTile * kD * 2;
constexpr int kStages = 5;
constexpr int kSub = 4;
constexpr int kSubBytes = kTileBytes / kSub;
constexpr int kPairEnd = 28;
constexpr int kOddXor = 7;

enum { L, F, R };
struct EndPiece { int kind, k0, nk, window; };
constexpr int kEnd = 9;
__host__ __device__ constexpr EndPiece end_piece(int y) {
    constexpr EndPiece e[kEnd] = {{L, 0, 4, 130}, {L, 4, 4, 136}, {F, 8, 2, 136}, {F, 10, 2, 135}, {F, 12, 2, 122},
                                  {F, 14, 2, 120}, {R, 0, 4, 119}, {R, 4, 2, 125}, {R, 6, 2, 155}};
    return e[y];
}
constexpr int kEndLeft = 5;
__host__ __device__ constexpr int end_offset(int y) {
    int o = 0;
    for (int j = 0; j < y; j++) o += end_piece(j).nk * (end_piece(j).kind == F ? 4096 : 2048);
    return o;
}
constexpr int kMain = (kItems - 2) * kSub;
constexpr int kEndSlot = (kItems - 2) % kStages;
static_assert(end_offset(kEnd) == 2 * kTileBytes && end_offset(4) == kTileBytes && kEndSlot + 1 < kStages, "end pieces");

__device__ __forceinline__ int main_window(int x) { return min(263, 142 + max((kMain - x) * 9 / 4, (kMain - x) * 5 - 66)); }
constexpr int kStartProgress = -260;
constexpr uint32_t kStartCount = 384;
constexpr uint32_t kRateP = 2750, kRateE = 3470;
constexpr uint32_t kBeta = 37;
constexpr int kWeight = 126;

constexpr int kOffQ = 0;
constexpr int kOffKt = 32768;
constexpr int kOffVt = kOffKt + 8192;
constexpr int kOffMask = kOffVt + 8192;
constexpr int kOffRing = kOffMask + 2048;
constexpr int kOffBar = kOffRing + kStages * kTileBytes;
constexpr int kOffTab = kOffBar + 512;
constexpr int kSmemBytes = kOffTab + 16 * (kMain + kEnd) + 1024;
constexpr int kThreads = 384;

__device__ unsigned int g_progress;

struct Maps { CUtensorMap k, v, vh64, vh32, q, kt, vt; };

__device__ __forceinline__ uint32_t smem_u32(const void* p) { return (uint32_t)__cvta_generic_to_shared(p); }

__device__ __forceinline__ void mbar_init(uint32_t bar, uint32_t cnt) {
    asm volatile("mbarrier.init.shared::cta.b64 [%0], %1;" ::"r"(bar), "r"(cnt) : "memory");
}
__device__ __forceinline__ void mbar_expect_tx(uint32_t bar, uint32_t bytes) {
    asm volatile("mbarrier.arrive.expect_tx.shared::cta.b64 _, [%0], %1;" ::"r"(bar), "r"(bytes) : "memory");
}
__device__ __forceinline__ void mbar_arrive(uint32_t bar) {
    asm volatile("mbarrier.arrive.shared::cta.b64 _, [%0];" ::"r"(bar) : "memory");
}
__device__ __forceinline__ void mbar_wait(uint32_t bar, uint32_t parity) {
    asm volatile(
        "{\n.reg .pred p, q;\n.reg .u32 n;\nmov.u32 n, 0;\n"
        "WAIT_%=:\n"
        "mbarrier.try_wait.parity.shared::cta.b64 p, [%0], %1;\n"
        "add.u32 n, n, 1;\n"
        "setp.lt.and.u32 q, n, %2, !p;\n"
        "@q bra WAIT_%=;\n}"
        ::"r"(bar), "r"(parity), "n"(0x20000) : "memory");
}

__device__ __forceinline__ void tma_load(uint32_t dst, const CUtensorMap* m, uint32_t bar, int half, int grp) {
    asm volatile(
        "cp.async.bulk.tensor.4d.shared::cluster.global.mbarrier::complete_tx::bytes [%0], [%1, {%3, %3, %4, %5}], [%2];"
        ::"r"(dst), "l"(m), "r"(bar), "r"(0), "r"(half), "r"(grp) : "memory");
}
__device__ __forceinline__ bool elect_one() {
    uint32_t p;
    asm volatile("{\n.reg .pred p;\nelect.sync _|p, 0xffffffff;\nselp.u32 %0, 1, 0, p;\n}" : "=r"(p));
    return p != 0;
}
__device__ __forceinline__ void prefetch_map(const CUtensorMap* m) {
    asm volatile("prefetch.tensormap [%0];" ::"l"(m) : "memory");
}

__device__ __forceinline__ uint64_t make_desc(uint32_t addr, uint32_t sbo) {
    return (uint64_t)((addr & 0x3FFFF) >> 4) | (1ull << 16) | ((uint64_t)(sbo >> 4) << 32) | (1ull << 62);
}

__device__ __forceinline__ void wg_fence() { asm volatile("wgmma.fence.sync.aligned;" ::: "memory"); }
__device__ __forceinline__ void wg_commit() { asm volatile("wgmma.commit_group.sync.aligned;" ::: "memory"); }
template <int N> __device__ __forceinline__ void wg_wait() { asm volatile("wgmma.wait_group.sync.aligned %0;" ::"n"(N) : "memory"); }
template <int LO, int HI, int N> __device__ __forceinline__ void fence_regs(float (&r)[N]) {
#pragma unroll
    for (int i = LO; i < HI; i++) asm volatile("" : "+f"(r[i])::"memory");
}
__device__ __forceinline__ void bar_sync(int id) { asm volatile("barrier.sync %0, 256;" ::"r"(id) : "memory"); }
__device__ __forceinline__ void bar_arrive(int id) { asm volatile("barrier.arrive %0, 256;" ::"r"(id) : "memory"); }

#define ACC8(d, o) "+f"(d[o]), "+f"(d[o + 1]), "+f"(d[o + 2]), "+f"(d[o + 3]), "+f"(d[o + 4]), "+f"(d[o + 5]), "+f"(d[o + 6]), "+f"(d[o + 7])
#define ACC32(d, o) ACC8(d, o), ACC8(d, o + 8), ACC8(d, o + 16), ACC8(d, o + 24)
#define REGS32                                                                \
    "{%0, %1, %2, %3, %4, %5, %6, %7, %8, %9, %10, %11, %12, %13, %14, %15, " \
    "%16, %17, %18, %19, %20, %21, %22, %23, %24, %25, %26, %27, %28, %29, %30, %31}"

template <int O>
__device__ __forceinline__ void wgmma_qk64(float (&d)[64], uint64_t da, uint64_t db, int acc) {
    asm volatile(
        "{\n.reg .pred p;\nsetp.ne.b32 p, %34, 0;\n"
        "wgmma.mma_async.sync.aligned.m64n64k16.f32.bf16.bf16 " REGS32 ", %32, %33, p, 1, 1, 0, 0;\n}"
        : ACC32(d, O) : "l"(da), "l"(db), "r"(acc));
}
__device__ __forceinline__ void wgmma_qk32(float (&d)[16], uint64_t da, uint64_t db, int acc) {
    asm volatile(
        "{\n.reg .pred p;\nsetp.ne.b32 p, %18, 0;\n"
        "wgmma.mma_async.sync.aligned.m64n32k16.f32.bf16.bf16 "
        "{%0, %1, %2, %3, %4, %5, %6, %7, %8, %9, %10, %11, %12, %13, %14, %15}, %16, %17, p, 1, 1, 0, 0;\n}"
        : ACC8(d, 0), ACC8(d, 8) : "l"(da), "l"(db), "r"(acc));
}
template <int O>
__device__ __forceinline__ void wgmma_pv64(float (&d)[64], const uint32_t* a, uint64_t db) {
    asm volatile(
        "{\n.reg .pred p;\nsetp.ne.b32 p, 1, 0;\n"
        "wgmma.mma_async.sync.aligned.m64n64k16.f32.bf16.bf16 " REGS32 ", {%32, %33, %34, %35}, %36, p, 1, 1, 1;\n}"
        : ACC32(d, O) : "r"(a[0]), "r"(a[1]), "r"(a[2]), "r"(a[3]), "l"(db));
}
__device__ __forceinline__ void pv_piece(float (&o)[64], const uint32_t* a, uint32_t addr) {
    const uint64_t dv = make_desc(addr, 2048);
    wg_fence();
    wgmma_pv64<0>(o, a, dv);
    wgmma_pv64<0>(o, a + 4, dv + (4096 >> 4));
    wg_commit();
    wgmma_pv64<32>(o, a, dv + (1024 >> 4));
    wgmma_pv64<32>(o, a + 4, dv + (5120 >> 4));
    wg_commit();
}

__device__ __forceinline__ float ex2(float x) {
    float y;
    asm("ex2.approx.ftz.f32 %0, %1;" : "=f"(y) : "f"(x));
    return y;
}
__device__ __forceinline__ float rcp(float x) {
    float y;
    asm("rcp.approx.ftz.f32 %0, %1;" : "=f"(y) : "f"(x));
    return y;
}
__device__ __forceinline__ uint32_t pack_bf16(float lo, float hi) {
    uint32_t r;
    asm("cvt.rn.bf16x2.f32 %0, %1, %2;" : "=r"(r) : "f"(hi), "f"(lo));
    return r;
}
__device__ __forceinline__ float quad_max(float x) {
    x = fmaxf(x, __shfl_xor_sync(0xffffffffu, x, 1));
    return fmaxf(x, __shfl_xor_sync(0xffffffffu, x, 2));
}
__device__ __forceinline__ float quad_sum(float x) {
    x += __shfl_xor_sync(0xffffffffu, x, 1);
    return x + __shfl_xor_sync(0xffffffffu, x, 2);
}

template <int V> struct IntC { static constexpr int value = V; };
template <int N, int I = 0, class Fn> __device__ __forceinline__ void static_for(Fn fn) {
    if constexpr (I < N) {
        fn(IntC<I>{});
        static_for<N, I + 1>(fn);
    }
}
constexpr uint64_t end_field(int f) {
    uint64_t m = 0;
    for (int y = 0; y < kEnd; y++) {
        const EndPiece e = end_piece(y);
        m |= (uint64_t)(f == 0 ? end_offset(y) / 4096 | (end_offset(y + 1) - end_offset(y)) / 4096 << 4
                        : f == 1 ? e.k0 | (e.kind == F ? 1 : e.nk == 4 ? 2 : 3) << 4 | (e.kind == R) << 6
                        : e.window - 64) << 7 * y;
    }
    return m;
}
constexpr uint64_t kEndOffs = end_field(0), kEndKeys = end_field(1), kEndWins = end_field(2);
constexpr int last_need() {
    int m = 0;
    for (int y = 0; y < kEnd; y++) {
        const int need = kMain * (kCtas / kSub) + end_offset(y) / 256 - end_piece(y).window;
        m = need > m ? need : m;
    }
    return m;
}
constexpr int kLastNeed = last_need();
struct Ring {
    int s;
    uint32_t ph;
    __device__ __forceinline__ void next() { if (++s == kStages) { s = 0; ph ^= 1; } }
};

__global__ void __launch_bounds__(kThreads, 1)
tree_attn_kernel(const __nv_bfloat16* __restrict__ q, const __nv_bfloat16* __restrict__ mask, __nv_bfloat16* __restrict__ out,
                 unsigned int* progress, const __grid_constant__ Maps tm) {
    extern __shared__ uint8_t smem_raw[];
    if (threadIdx.x == 0)
        asm volatile("cp.async.bulk.prefetch.L2.global [%0], 32768;" ::"l"(q + (size_t)blockIdx.x * kRows * kD));
    const uint32_t sb = (smem_u32(smem_raw) + 1023u) & ~1023u;
    const uint32_t bar_q = sb + kOffBar;
    const uint32_t bar_empty = bar_q + 8;
    const uint32_t bar_full = bar_empty + 64;
    const uint32_t bar_end = bar_full + 8 * kStages * kSub;
    const uint32_t pace_slot = sb + kOffBar + 448;
    static_assert(kStages <= 8 && kStages * kSub + kEnd <= 32, "barriers");
    const int cta = blockIdx.x;

    if (threadIdx.x == 256) {
        mbar_init(bar_q, 1);
        asm volatile("fence.mbarrier_init.release.cluster;" ::: "memory");
        mbar_expect_tx(bar_q, 32768 + 16384 + 2048);
        tma_load(sb + kOffQ, &tm.q, bar_q, 0, cta * (kRows / 8));
        tma_load(sb + kOffKt, &tm.kt, bar_q, 0, cta * (kT / 8));
        tma_load(sb + kOffVt, &tm.vt, bar_q, 0, cta * (kT / 8));
        asm volatile("cp.async.bulk.shared::cluster.global.mbarrier::complete_tx::bytes [%0], [%1], 2048, [%2];"
                     ::"r"(sb + kOffMask), "l"(mask + (cta / kHkv) * kT * kT), "r"(bar_q) : "memory");
    }
    __syncwarp();
    const int warp = __shfl_sync(0xffffffffu, threadIdx.x >> 5, 0);
    const int lane = threadIdx.x & 31;
    auto put_entry = [&](int x, uint32_t e0, uint32_t e1, uint32_t e2, uint32_t e3) {
        asm volatile("st.shared.v4.u32 [%0], {%1, %2, %3, %4};" ::"r"(sb + kOffTab + 16 * x),
                     "r"(cta * (kC / 8) + (e0 ^ (cta & 1) * kOddXor * 8)), "r"(e1), "r"(e2 + sb + kOffRing), "r"(e3) : "memory");
    };

    if (warp >= 8) {
        asm volatile("setmaxnreg.dec.sync.aligned.u32 40;");
        if (warp == 8) {
            asm volatile("barrier.sync 7, 384;" ::: "memory");
            if (elect_one()) {
                uint32_t ta = sb + kOffTab;
#pragma unroll 1
                do {
                    uint32_t e0, e1, e2, e3;
                    asm volatile("ld.shared.v4.u32 {%0, %1, %2, %3}, [%4];" : "=r"(e0), "=r"(e1), "=r"(e2), "=r"(e3) : "r"(ta) : "memory");
                    if ((int)e3 < 0) mbar_wait(bar_empty + ((e3 >> 16) & 0xff), (e3 >> 30) & 1);
                    uint32_t dst = e2 & 0xffffff, bar = bar_full + (e3 & 0xffff), half = e0 >> 31, grp = e0 & 0x7fffffff;
                    const char* map = reinterpret_cast<const char*>(&tm) + (e1 & 0xffff);
                    mbar_expect_tx(bar, (e2 >> 24) << 10);
                    asm volatile("" : "+r"(dst), "+r"(bar), "+r"(half), "+r"(grp), "+l"(map)::"memory");
                    for (int n = 0; n < 0x100000; n++) {
                        uint32_t g, t;
                        asm volatile("ld.volatile.shared.v2.u32 {%0, %1}, [%2];" : "=r"(g), "=r"(t) : "r"(pace_slot) : "memory");
                        if ((int)g + (int)((min((uint32_t)clock() - t, 12000u) * kRateP) >> 16) >= (int)e1 >> 16) break;
                    }
                    tma_load(dst, reinterpret_cast<const CUtensorMap*>(map), bar, half, grp);
                    ta += 16;
                } while (ta < sb + kOffTab + 16 * (kMain + kEnd));
            }
        } else if (warp == 9) {
            uint32_t t_est = clock();
            if (lane == 0) {
                asm volatile("st.shared.v4.u32 [%0], {%1, %2, %3, %3};" ::"r"(pace_slot), "r"(kStartProgress), "r"(t_est), "r"(0) : "memory");
                prefetch_map(&tm.k);
                prefetch_map(&tm.v);
                prefetch_map(&tm.vh64);
                prefetch_map(&tm.vh32);
            }
            __syncwarp();
            asm volatile("barrier.arrive 7, 384;" ::: "memory");
            if (lane == 0) {
                int est = kStartProgress * 256;
                uint32_t g_mark = 0, t_mark = t_est;
                do {
                    uint32_t g, t = clock();
                    asm volatile("ld.relaxed.gpu.global.u32 %0, [%1];" : "=r"(g) : "l"(progress) : "memory");
                    asm volatile("st.volatile.shared.u32 [%0], %1;" ::"r"(pace_slot + 24), "r"(g) : "memory");
                    t += (((uint32_t)clock() - t) * kBeta) >> 8;
                    est += (int)(((t - t_est) * kRateE) >> 8);
                    if (g >= kStartCount) est += (((int)(g << 8) - est) * kWeight) >> 8;
                    t_est = t;
                    if (g - g_mark >= 4 * kCtas) { g_mark = g; t_mark = t; }
                    if (t - t_mark > 60000u) est = kLastNeed * 256;
                    asm volatile("st.volatile.shared.v2.u32 [%0], {%1, %2};" ::"r"(pace_slot), "r"(est >> 8), "r"(t) : "memory");
                } while (est < kLastNeed * 256);
            }
        } else if (warp == 10) {
            asm volatile("barrier.sync 7, 384;" ::: "memory");
            if (lane == 0) {
                Ring r{0, 0};
#pragma unroll 1
                for (int i = 0; i < kItems; i++) {
                    const int y = (i - (kItems - 2)) * kSub + (cta & 3);
                    mbar_wait(y < 0 ? bar_full + 8 * (kSub * r.s + (cta & 3)) : bar_end + 8 * (y + (y == 7)), y < 0 ? r.ph : 0);
                    asm volatile("red.relaxed.gpu.global.inc.u32 [%0], %1;" ::"l"(progress), "n"(kCtas * kItems - 1) : "memory");
                    mbar_arrive(bar_empty + 8 * r.s);
                    r.next();
                }
            }
        } else {
            if (lane < kEnd) {
                const uint32_t of = kEndOffs >> 7 * lane, ky = kEndKeys >> 7 * lane, wn = kEndWins >> 7 * lane;
                constexpr uint32_t kPar = (((kItems - 2) / kStages) & 1) ^ 1;
                static_assert((kItems - 2) / kStages == (kItems - 1) / kStages, "parity");
                put_entry(kMain + lane, (kC / 8 - 32 + 2 * (ky & 15)) | (ky & 64) << 25,
                          (kMain * (kCtas / kSub) + (of & 15) * 16 - 64 - (wn & 127)) << 16 | ((ky >> 4) & 3) * 128,
                          (kEndSlot * kTileBytes + (of & 15) * 4096) | ((of >> 4) & 7) << 26,
                          8 * (kStages * kSub + lane) | 8 * (kEndSlot + (lane >> 2)) << 16 | kPar << 30 | (uint32_t)((lane & ~4) == 0) << 31);
            }
            __syncwarp();
            asm volatile("barrier.arrive 7, 384;" ::: "memory");
        }
    } else {
        if (threadIdx.x < kMain) {
            const int x = threadIdx.x, i = x >> 2, u = x & 3;
            const bool isv = i < 2 * kPairEnd ? (i & 2) != 0 : i > 2 * kPairEnd && !(i & 1);
            const int tile = i < 2 * kPairEnd ? (i >> 2) * 2 + (i & 1) : (isv ? (i >> 1) - 1 : (i + 1) >> 1);
            const int n = i / kStages, s = i - n * kStages;
            put_entry(x, tile * (kTile / 8) + 4 * u, (uint32_t)(x * (kCtas / kSub) - main_window(x)) << 16 | isv * 128,
                      (s * kSub + u) * kSubBytes | 8 << 24,
                      8 * (s * kSub + u) | 8 * s << 16 | (uint32_t)((n & 1) ^ 1) << 30 | (uint32_t)(u == 0) << 31);
        }
        __syncwarp();
        if (elect_one()) {
            mbar_init(bar_empty + 8 * warp, 9);
#pragma unroll
            for (int j = 0; j < 4; j++) mbar_init(bar_full + 8 * (4 * warp + j), 1);
            asm volatile("fence.mbarrier_init.release.cluster;" ::: "memory");
        }
        __syncwarp();
        asm volatile("barrier.sync 7, 384;" ::: "memory");
        asm volatile("setmaxnreg.inc.sync.aligned.u32 232;");
        const int wg = warp >> 2;
        const float kScale = 0.08838834764831845f;
        const float kLog2e = 1.4426950408889634f;
        const float c = kScale * kLog2e;
        if (wg == 1) {
            bar_arrive(1);
            bar_arrive(3);
        }

        const uint64_t dq = make_desc(sb + kOffQ + wg * 16384, 2048);
        float o[64], sc[64];
        uint32_t p[64];
        float l0, l1, a0 = 1.f, a1 = 1.f;
        bool moved = true;
        Ring r{0, 0};
#pragma unroll
        for (int i = 0; i < 64; i++) o[i] = sc[i] = 0.f;
#pragma unroll
        for (int i = 0; i < 32; i++) p[i] = 0;
        float m0, m1;
        mbar_wait(bar_q, 0);
        {
            float st[16];
            const uint64_t dk = make_desc(sb + kOffKt, 2048);
            wg_fence();
#pragma unroll
            for (int k = 0; k < 8; k++) {
                const uint32_t off = ((k >> 2) * 1024 + (k & 3) * 32) >> 4;
                wgmma_qk32(st, dq + off, dk + off, k != 0);
            }
            wg_commit();
            wg_wait<0>();
            fence_regs<0, 16>(st);
#pragma unroll
            for (int i = 0; i < 4; i++) {
#pragma unroll
                for (int h = 0; h < 2; h++) {
                    uint32_t w;
                    asm volatile("ld.shared.u32 %0, [%1];" : "=r"(w)
                                 : "r"(sb + kOffMask + ((warp & 1) * 16 + (lane >> 2) + 8 * h) * 64 + 16 * i + 4 * (lane & 3)));
                    const float ma = __uint_as_float(w << 16), mb = __uint_as_float(w & 0xffff0000u);
                    st[4 * i + 2 * h] = (st[4 * i + 2 * h] * kScale + (1.0f - ma) * -1.0e9f) * kLog2e;
                    st[4 * i + 2 * h + 1] = (st[4 * i + 2 * h + 1] * kScale + (1.0f - mb) * -1.0e9f) * kLog2e;
                }
            }
            m0 = fmaxf(st[0], st[1]);
            m1 = fmaxf(st[2], st[3]);
#pragma unroll
            for (int i = 1; i < 4; i++) {
                m0 = fmaxf(m0, fmaxf(st[4 * i], st[4 * i + 1]));
                m1 = fmaxf(m1, fmaxf(st[4 * i + 2], st[4 * i + 3]));
            }
            m0 = quad_max(m0);
            m1 = quad_max(m1);
            l0 = 0.f;
            l1 = 0.f;
#pragma unroll
            for (int i = 0; i < 4; i++) {
                const float a = ex2(st[4 * i] - m0), b = ex2(st[4 * i + 1] - m0);
                const float e = ex2(st[4 * i + 2] - m1), f = ex2(st[4 * i + 3] - m1);
                l0 += a + b;
                l1 += e + f;
                p[2 * i] = pack_bf16(a, b);
                p[2 * i + 1] = pack_bf16(e, f);
            }
        }
        bool pending = true;
#pragma unroll 1
        for (int kt = 0;;) {
            const bool pv_only = pending && kt > 0 && !(kt & 1) && kt <= kPairEnd;
            const bool tree = kt == 0;
            const bool hand_over = wg == 0 || kt < kTiles - 1;
            if (!pv_only) {
                const uint64_t dk = make_desc(sb + kOffRing + r.s * kTileBytes, 2048);
                mbar_wait(bar_full + 8 * (r.s * kSub), r.ph);
                mbar_wait(bar_full + 8 * (r.s * kSub + 1), r.ph);
                wg_fence();
#pragma unroll
                for (int k = 0; k < 8; k++) {
                    const uint32_t off = ((k >> 2) * 1024 + (k & 3) * 32) >> 4;
                    wgmma_qk64<0>(sc, dq + off, dk + off, k != 0);
                }
                wg_commit();
                mbar_wait(bar_full + 8 * (r.s * kSub + 2), r.ph);
                mbar_wait(bar_full + 8 * (r.s * kSub + 3), r.ph);
                bar_sync(1 + wg);
                wg_fence();
#pragma unroll
                for (int k = 0; k < 8; k++) {
                    const uint32_t off = ((k >> 2) * 1024 + (k & 3) * 32) >> 4;
                    wgmma_qk64<32>(sc, dq + off, dk + (16384 >> 4) + off, k != 0);
                }
                wg_commit();
                if (hand_over) bar_arrive(2 - wg);
                wg_wait<1>();
                fence_regs<0, 32>(sc);
                float x0 = fmaxf(sc[0], sc[1]), x1 = fmaxf(sc[2], sc[3]);
#pragma unroll
                for (int i = 1; i < 8; i++) {
                    x0 = fmaxf(x0, fmaxf(sc[4 * i], sc[4 * i + 1]));
                    x1 = fmaxf(x1, fmaxf(sc[4 * i + 2], sc[4 * i + 3]));
                }
                asm volatile("" : "+f"(x0), "+f"(x1)::"memory");
                wg_wait<0>();
                fence_regs<32, 64>(sc);
                if (lane == 0) mbar_arrive(bar_empty + 8 * r.s);
                r.next();

#pragma unroll
                for (int i = 8; i < 16; i++) {
                    x0 = fmaxf(x0, fmaxf(sc[4 * i], sc[4 * i + 1]));
                    x1 = fmaxf(x1, fmaxf(sc[4 * i + 2], sc[4 * i + 3]));
                }
                float n0 = fmaxf(m0, quad_max(x0) * c), n1 = fmaxf(m1, quad_max(x1) * c);
                moved = __any_sync(0xffffffffu, n0 > m0 || n1 > m1);
                {
                    float z;
                    asm volatile("st.volatile.shared.f32 [%2 + 4], %3;\n"
                                 "barrier.sync %1, 256;\nld.volatile.shared.f32 %0, [%2];"
                                 : "=f"(z) : "r"(3 + wg), "r"(pace_slot + 12), "f"(n0 + n1) : "memory");
                    n0 += z;
                    n1 += z;
                }
                a0 = ex2(m0 - n0);
                a1 = ex2(m1 - n1);
                m0 = n0;
                m1 = n1;
                l0 *= a0;
                l1 *= a1;
#pragma unroll
                for (int i = 0; i < 16; i++) {
                    sc[4 * i] = ex2(fmaf(sc[4 * i], c, -n0));
                    sc[4 * i + 1] = ex2(fmaf(sc[4 * i + 1], c, -n0));
                    sc[4 * i + 2] = ex2(fmaf(sc[4 * i + 2], c, -n1));
                    sc[4 * i + 3] = ex2(fmaf(sc[4 * i + 3], c, -n1));
                    l0 += sc[4 * i] + sc[4 * i + 1];
                    l1 += sc[4 * i + 2] + sc[4 * i + 3];
                }
                {
                    asm volatile("st.volatile.shared.f32 [%0], %1;" ::"r"(pace_slot + 16), "f"(sc[59]) : "memory");
                    if (hand_over) bar_arrive(4 - wg);
                }
                if (++kt == kTiles) break;
            }

            if (pending) {
                const uint32_t vslot = sb + kOffRing + r.s * kTileBytes;
                const uint32_t vbar = bar_full + 8 * (r.s * kSub);
                if (!tree) mbar_wait(vbar, r.ph);
                pv_piece(o, p, tree ? sb + kOffVt : vslot);
                if (!tree) {
#pragma unroll
                    for (int u = 1; u < 4; u++) {
                        mbar_wait(vbar + 8 * u, r.ph);
                        pv_piece(o, p + 8 * u, vslot + u * kSubBytes);
                    }
                }
            }
            wg_wait<0>();
            fence_regs<0, 64>(o);
            if (pending && !tree) {
                if (lane == 0) mbar_arrive(bar_empty + 8 * r.s);
                r.next();
            }
            pending = !pv_only;
            if (!pv_only) {
                if (moved) {
#pragma unroll
                    for (int i = 0; i < 16; i++) {
                        o[4 * i] *= a0;
                        o[4 * i + 1] *= a0;
                        o[4 * i + 2] *= a1;
                        o[4 * i + 3] *= a1;
                    }
                }
#pragma unroll
                for (int i = 0; i < 16; i++) {
                    p[2 * i] = pack_bf16(sc[4 * i], sc[4 * i + 1]);
                    p[2 * i + 1] = pack_bf16(sc[4 * i + 2], sc[4 * i + 3]);
                }
            }
        }

#pragma unroll
        for (int h = 0; h < 2; h++) {
            const float a = h ? a1 : a0;
            if (__any_sync(0xffffffffu, a != 1.f)) {
                const uint32_t hi = pack_bf16(a, a);
                const float rest = a - __uint_as_float(hi << 16);
                const uint32_t lo = pack_bf16(rest, rest);
#pragma unroll
                for (int i = 0; i < 16; i++) {
                    o[4 * i + 2 * h] *= a;
                    o[4 * i + 2 * h + 1] *= a;
                    asm("{\n.reg .b32 t;\nmul.rn.bf16x2 t, %0, %2;\nfma.rn.bf16x2 %0, %0, %1, t;\n}" : "+r"(p[2 * i + h]) : "r"(hi), "r"(lo));
                }
            }
        }
        float i0, i1;
        const uint32_t stg = sb + kOffQ + warp * 4096;
        const uint32_t swz = ((lane >> 3) ^ (lane & 7)) << 4;
        uint32_t sa = stg + (lane & 7) * 128 + swz, sa2 = sa ^ 64;
        uint32_t la = stg + (lane >> 3) * 128 + swz, la2 = (la ^ 64) + 512;
        uint4* gp = reinterpret_cast<uint4*>(out + (size_t)(cta * kRows + warp * 16 + (lane >> 3)) * kD) + (lane & 7);
        asm volatile("" : "+r"(sa), "+r"(sa2), "+r"(la), "+r"(la2), "+l"(gp));
        uint4 vv[4] = {};
        auto put = [&](int j, int h) {
            asm volatile("st.global.v4.u32 [%0], {%1, %2, %3, %4};"
                         ::"l"(gp + 64 * j + 8 * h), "r"(vv[j].x), "r"(vv[j].y), "r"(vv[j].z), "r"(vv[j].w) : "memory");
        };
        auto store_half = [&](auto hc) {
            constexpr int h = decltype(hc)::value;
#pragma unroll
            for (int hr = 0; hr < 2; hr++) {
                const float f = hr ? i1 : i0;
#pragma unroll
                for (int i = 0; i < 2; i++) {
                    const float* v = o + 32 * h + 16 * i + 2 * hr;
                    asm volatile("stmatrix.sync.aligned.m8n8.x4.shared.b16 [%0], {%1, %2, %3, %4};"
                                 ::"r"((i ? sa2 : sa) + hr * 1024 + h * 2048), "r"(pack_bf16(v[0] * f, v[1] * f)),
                                   "r"(pack_bf16(v[4] * f, v[5] * f)), "r"(pack_bf16(v[8] * f, v[9] * f)),
                                   "r"(pack_bf16(v[12] * f, v[13] * f)) : "memory");
                }
                __syncwarp();
                uint4* v = vv + 2 * hr;
#pragma unroll
                for (int i = 0; i < 2; i++)
                    asm volatile("ld.volatile.shared.v4.u32 {%0, %1, %2, %3}, [%4];" : "=r"(v[i].x), "=r"(v[i].y), "=r"(v[i].z), "=r"(v[i].w)
                                 : "r"((i ? la2 : la) + hr * 1024 + h * 2048) : "memory");
                if (h || !hr) {
                    put(2 * hr, h);
                    put(2 * hr + 1, h);
                }
            }
        };
        auto pack_last = [&]() {
            i0 = rcp(quad_sum(l0));
            i1 = rcp(quad_sum(l1));
#pragma unroll
            for (int i = 0; i < 16; i++) {
                p[32 + 2 * i] = pack_bf16(sc[4 * i], sc[4 * i + 1]);
                p[32 + 2 * i + 1] = pack_bf16(sc[4 * i + 2], sc[4 * i + 3]);
            }
#pragma unroll
            for (int i = 32; i < 64; i++) asm volatile("" : "+r"(p[i])::"memory");
            asm volatile("" : "+f"(i0), "+f"(i1)::"memory");
        };
        const uint64_t dend = make_desc(sb + kOffRing + kEndSlot * kTileBytes, 1024);
        static_for<kEnd>([&](auto yc) {
            constexpr int y = yc.value;
            constexpr EndPiece e = end_piece(y);
            constexpr int step = e.kind == F ? 4096 : 2048;
            const uint64_t dv = dend + (end_offset(y) >> 4) + (e.kind == F ? (uint64_t)(1024 >> 4) << 32 : 0);
            mbar_wait(bar_end + 8 * y, 0);
            wg_fence();
            if (e.kind != R) {
#pragma unroll
                for (int k = 0; k < e.nk; k++) wgmma_pv64<0>(o, p + 4 * (e.k0 + k), dv + ((k * step) >> 4));
                wg_commit();
            }
            if (e.kind != L) {
#pragma unroll
                for (int k = 0; k < e.nk; k++) wgmma_pv64<32>(o, p + 4 * (e.k0 + k), dv + ((k * step + (e.kind == F ? 1024 : 0)) >> 4));
                wg_commit();
            }
            if (y == 0) pack_last();
            if (y == kEndLeft + 1) {
                put(2, 0);
                put(3, 0);
            }
            if (y == kEndLeft) {
                wg_wait<1>();
                fence_regs<0, 32>(o);
                store_half(IntC<0>{});
            }
        });
        wg_wait<0>();
        fence_regs<32, 64>(o);
        store_half(IntC<1>{});
    }
}

typedef CUresult (*EncodeFn)(CUtensorMap*, CUtensorMapDataType, cuuint32_t, void*, const cuuint64_t*,
                             const cuuint64_t*, const cuuint32_t*, const cuuint32_t*, CUtensorMapInterleave,
                             CUtensorMapSwizzle, CUtensorMapL2promotion, CUtensorMapFloatOOBfill);

void make_map(EncodeFn enc, CUtensorMap* m, const void* p, uint64_t rows, uint32_t box_rows, uint32_t halves) {
    const cuuint64_t dims[4] = {64, 8, 2, rows / 8};
    const cuuint64_t strides[3] = {256, 128, 2048};
    const cuuint32_t box[4] = {64, 8, halves, box_rows / 8};
    const cuuint32_t es[4] = {1, 1, 1, 1};
    enc(m, CU_TENSOR_MAP_DATA_TYPE_BFLOAT16, 4, const_cast<void*>(p), dims, strides, box, es,
        CU_TENSOR_MAP_INTERLEAVE_NONE, CU_TENSOR_MAP_SWIZZLE_128B,
        halves == 2 ? CU_TENSOR_MAP_L2_PROMOTION_L2_256B : CU_TENSOR_MAP_L2_PROMOTION_L2_128B,
        CU_TENSOR_MAP_FLOAT_OOB_FILL_NONE);
}

}

extern "C" void kernel_launch(void* const* d_in, const int* in_sizes, int n_in, void* d_out, int out_size) {
    (void)in_sizes; (void)n_in; (void)out_size;
    static EncodeFn enc = nullptr;
    static unsigned int* progress = nullptr;
    if (!enc) {
        cudaDriverEntryPointQueryResult qr;
        cudaGetDriverEntryPoint("cuTensorMapEncodeTiled", (void**)&enc, cudaEnableDefault, &qr);
        cudaFuncSetAttribute(tree_attn_kernel, cudaFuncAttributeMaxDynamicSharedMemorySize, kSmemBytes);
        cudaGetSymbolAddress((void**)&progress, g_progress);
    }
    Maps tm;
    make_map(enc, &tm.q, d_in[0], (uint64_t)kCtas * kRows, kRows, 2);
    make_map(enc, &tm.k, d_in[1], (uint64_t)kCtas * kC, 32, 2);
    make_map(enc, &tm.v, d_in[2], (uint64_t)kCtas * kC, 32, 2);
    make_map(enc, &tm.vh64, d_in[2], (uint64_t)kCtas * kC, 64, 1);
    make_map(enc, &tm.vh32, d_in[2], (uint64_t)kCtas * kC, 32, 1);
    make_map(enc, &tm.kt, d_in[3], (uint64_t)kCtas * kT, kT, 2);
    make_map(enc, &tm.vt, d_in[4], (uint64_t)kCtas * kT, kT, 2);
    tree_attn_kernel<<<kCtas, kThreads, kSmemBytes, cudaStreamPerThread>>>(
        (const __nv_bfloat16*)d_in[0], (const __nv_bfloat16*)d_in[5], (__nv_bfloat16*)d_out, progress, tm);
}
```

```cpp
#include <cuda_runtime.h>
#include <cuda_bf16.h>
#include <cuda.h>
#include <stddef.h>
#include <stdint.h>

namespace {

constexpr int kB = 16, kHq = 32, kHkv = 8, kT = 32, kC = 4096, kD = 128;
constexpr int kCtas = kB * kHkv;
constexpr int kRows = (kHq / kHkv) * kT;
constexpr int kTile = 128;
constexpr int kTiles = kC / kTile;
constexpr int kItems = 2 * kTiles;
constexpr int kTileBytes = kTile * kD * 2;
constexpr int kStages = 5;
constexpr int kSub = 4;
constexpr int kSubBytes = kTileBytes / kSub;
constexpr int kPairEnd = 28;
constexpr uint32_t kOddXor = 348, kOddXorEnd = 56;

enum { L, F, R };
struct EndPiece { int kind, k0, nk, window; };
constexpr int kEnd = 9;
__host__ __device__ constexpr EndPiece end_piece(int y) {
    constexpr EndPiece e[kEnd] = {{L, 0, 4, 130}, {L, 4, 4, 136}, {F, 8, 2, 136}, {F, 10, 2, 135}, {F, 12, 2, 122},
                                  {F, 14, 2, 120}, {R, 0, 4, 119}, {R, 4, 2, 125}, {R, 6, 2, 155}};
    return e[y];
}
constexpr int kEndLeft = 5;
__host__ __device__ constexpr int end_offset(int y) {
    int o = 0;
    for (int j = 0; j < y; j++) o += end_piece(j).nk * (end_piece(j).kind == F ? 4096 : 2048);
    return o;
}
constexpr int kMain = (kItems - 2) * kSub;
constexpr int kEndSlot = (kItems - 2) % kStages;
static_assert(end_offset(kEnd) == 2 * kTileBytes && end_offset(4) == kTileBytes && kEndSlot + 1 < kStages, "end pieces");

__device__ __forceinline__ int main_window(int x) { return min(240, 142 + max((kMain - x) * 9 / 4, (kMain - x) * 5 - 66)); }
constexpr int kStartProgress = -260;
constexpr uint32_t kStartCount = 384;
constexpr uint32_t kRateP = 2750, kRateE = 3470;
constexpr uint32_t kBeta = 37;
constexpr int kWeight = 126;

constexpr int kOffQ = 0;
constexpr int kOffKt = 32768;
constexpr int kOffVt = kOffKt + 8192;
constexpr int kOffMask = kOffVt + 8192;
constexpr int kOffRing = kOffMask + 2048;
constexpr int kOffBar = kOffRing + kStages * kTileBytes;
constexpr int kOffTab = kOffBar + 512;
constexpr int kSmemBytes = kOffTab + 16 * (kMain + kEnd) + 1024;
constexpr int kThreads = 384;

__device__ unsigned int g_progress;

struct Maps { CUtensorMap k, v, vh64, vh32, q, kt, vt; };

__device__ __forceinline__ uint32_t smem_u32(const void* p) { return (uint32_t)__cvta_generic_to_shared(p); }

__device__ __forceinline__ void mbar_init(uint32_t bar, uint32_t cnt) {
    asm volatile("mbarrier.init.shared::cta.b64 [%0], %1;" ::"r"(bar), "r"(cnt) : "memory");
}
__device__ __forceinline__ void mbar_expect_tx(uint32_t bar, uint32_t bytes) {
    asm volatile("mbarrier.arrive.expect_tx.shared::cta.b64 _, [%0], %1;" ::"r"(bar), "r"(bytes) : "memory");
}
__device__ __forceinline__ void mbar_arrive(uint32_t bar) {
    asm volatile("mbarrier.arrive.shared::cta.b64 _, [%0];" ::"r"(bar) : "memory");
}
__device__ __forceinline__ void mbar_wait(uint32_t bar, uint32_t parity) {
    asm volatile(
        "{\n.reg .pred p, q;\n.reg .u32 n;\nmov.u32 n, 0;\n"
        "WAIT_%=:\n"
        "mbarrier.try_wait.parity.shared::cta.b64 p, [%0], %1;\n"
        "add.u32 n, n, 1;\n"
        "setp.lt.and.u32 q, n, %2, !p;\n"
        "@q bra WAIT_%=;\n}"
        ::"r"(bar), "r"(parity), "n"(0x20000) : "memory");
}

__device__ __forceinline__ void tma_load(uint32_t dst, const CUtensorMap* m, uint32_t bar, int half, int grp) {
    asm volatile(
        "cp.async.bulk.tensor.4d.shared::cluster.global.mbarrier::complete_tx::bytes [%0], [%1, {%3, %3, %4, %5}], [%2];"
        ::"r"(dst), "l"(m), "r"(bar), "r"(0), "r"(half), "r"(grp) : "memory");
}
__device__ __forceinline__ bool elect_one() {
    uint32_t p;
    asm volatile("{\n.reg .pred p;\nelect.sync _|p, 0xffffffff;\nselp.u32 %0, 1, 0, p;\n}" : "=r"(p));
    return p != 0;
}
__device__ __forceinline__ void prefetch_map(const CUtensorMap* m) {
    asm volatile("prefetch.tensormap [%0];" ::"l"(m) : "memory");
}

__device__ __forceinline__ uint64_t make_desc(uint32_t addr, uint32_t sbo) {
    return (uint64_t)((addr & 0x3FFFF) >> 4) | (1ull << 16) | ((uint64_t)(sbo >> 4) << 32) | (1ull << 62);
}

__device__ __forceinline__ void wg_fence() { asm volatile("wgmma.fence.sync.aligned;" ::: "memory"); }
__device__ __forceinline__ void wg_commit() { asm volatile("wgmma.commit_group.sync.aligned;" ::: "memory"); }
template <int N> __device__ __forceinline__ void wg_wait() { asm volatile("wgmma.wait_group.sync.aligned %0;" ::"n"(N) : "memory"); }
template <int LO, int HI, int N> __device__ __forceinline__ void fence_regs(float (&r)[N]) {
#pragma unroll
    for (int i = LO; i < HI; i++) asm volatile("" : "+f"(r[i])::"memory");
}
__device__ __forceinline__ void bar_sync(int id) { asm volatile("barrier.sync %0, 256;" ::"r"(id) : "memory"); }
__device__ __forceinline__ void bar_arrive(int id) { asm volatile("barrier.arrive %0, 256;" ::"r"(id) : "memory"); }

#define ACC8(d, o) "+f"(d[o]), "+f"(d[o + 1]), "+f"(d[o + 2]), "+f"(d[o + 3]), "+f"(d[o + 4]), "+f"(d[o + 5]), "+f"(d[o + 6]), "+f"(d[o + 7])
#define ACC32(d, o) ACC8(d, o), ACC8(d, o + 8), ACC8(d, o + 16), ACC8(d, o + 24)
#define REGS32                                                                \
    "{%0, %1, %2, %3, %4, %5, %6, %7, %8, %9, %10, %11, %12, %13, %14, %15, " \
    "%16, %17, %18, %19, %20, %21, %22, %23, %24, %25, %26, %27, %28, %29, %30, %31}"

template <int O>
__device__ __forceinline__ void wgmma_qk64(float (&d)[64], uint64_t da, uint64_t db, int acc) {
    asm volatile(
        "{\n.reg .pred p;\nsetp.ne.b32 p, %34, 0;\n"
        "wgmma.mma_async.sync.aligned.m64n64k16.f32.bf16.bf16 " REGS32 ", %32, %33, p, 1, 1, 0, 0;\n}"
        : ACC32(d, O) : "l"(da), "l"(db), "r"(acc));
}
__device__ __forceinline__ void wgmma_qk32(float (&d)[16], uint64_t da, uint64_t db, int acc) {
    asm volatile(
        "{\n.reg .pred p;\nsetp.ne.b32 p, %18, 0;\n"
        "wgmma.mma_async.sync.aligned.m64n32k16.f32.bf16.bf16 "
        "{%0, %1, %2, %3, %4, %5, %6, %7, %8, %9, %10, %11, %12, %13, %14, %15}, %16, %17, p, 1, 1, 0, 0;\n}"
        : ACC8(d, 0), ACC8(d, 8) : "l"(da), "l"(db), "r"(acc));
}
template <int O>
__device__ __forceinline__ void wgmma_pv64(float (&d)[64], const uint32_t* a, uint64_t db) {
    asm volatile(
        "{\n.reg .pred p;\nsetp.ne.b32 p, 1, 0;\n"
        "wgmma.mma_async.sync.aligned.m64n64k16.f32.bf16.bf16 " REGS32 ", {%32, %33, %34, %35}, %36, p, 1, 1, 1;\n}"
        : ACC32(d, O) : "r"(a[0]), "r"(a[1]), "r"(a[2]), "r"(a[3]), "l"(db));
}
__device__ __forceinline__ void pv_piece(float (&o)[64], const uint32_t* a, uint32_t addr) {
    const uint64_t dv = make_desc(addr, 2048);
    wg_fence();
    wgmma_pv64<0>(o, a, dv);
    wgmma_pv64<0>(o, a + 4, dv + (4096 >> 4));
    wg_commit();
    wgmma_pv64<32>(o, a, dv + (1024 >> 4));
    wgmma_pv64<32>(o, a + 4, dv + (5120 >> 4));
    wg_commit();
}

__device__ __forceinline__ float ex2(float x) {
    float y;
    asm("ex2.approx.ftz.f32 %0, %1;" : "=f"(y) : "f"(x));
    return y;
}
__device__ __forceinline__ float rcp(float x) {
    float y;
    asm("rcp.approx.ftz.f32 %0, %1;" : "=f"(y) : "f"(x));
    return y;
}
__device__ __forceinline__ uint32_t pack_bf16(float lo, float hi) {
    uint32_t r;
    asm("cvt.rn.bf16x2.f32 %0, %1, %2;" : "=r"(r) : "f"(hi), "f"(lo));
    return r;
}
__device__ __forceinline__ float quad_max(float x) {
    x = fmaxf(x, __shfl_xor_sync(0xffffffffu, x, 1));
    return fmaxf(x, __shfl_xor_sync(0xffffffffu, x, 2));
}
__device__ __forceinline__ float quad_sum(float x) {
    x += __shfl_xor_sync(0xffffffffu, x, 1);
    return x + __shfl_xor_sync(0xffffffffu, x, 2);
}

template <int V> struct IntC { static constexpr int value = V; };
template <int N, int I = 0, class Fn> __device__ __forceinline__ void static_for(Fn fn) {
    if constexpr (I < N) {
        fn(IntC<I>{});
        static_for<N, I + 1>(fn);
    }
}
constexpr uint64_t end_field(int f) {
    uint64_t m = 0;
    for (int y = 0; y < kEnd; y++) {
        const EndPiece e = end_piece(y);
        m |= (uint64_t)(f == 0 ? end_offset(y) / 4096 | (end_offset(y + 1) - end_offset(y)) / 4096 << 4
                        : f == 1 ? e.k0 | (e.kind == F ? 1 : e.nk == 4 ? 2 : 3) << 4 | (e.kind == R) << 6
                        : e.window - 64) << 7 * y;
    }
    return m;
}
constexpr uint64_t kEndOffs = end_field(0), kEndKeys = end_field(1), kEndWins = end_field(2);
constexpr int last_need() {
    int m = 0;
    for (int y = 0; y < kEnd; y++) {
        const int need = kMain * (kCtas / kSub) + end_offset(y) / 256 - end_piece(y).window;
        m = need > m ? need : m;
    }
    return m;
}
constexpr int kLastNeed = last_need();
struct Ring {
    int s;
    uint32_t ph;
    __device__ __forceinline__ void next() { if (++s == kStages) { s = 0; ph ^= 1; } }
};

__global__ void __launch_bounds__(kThreads, 1)
tree_attn_kernel(const __nv_bfloat16* __restrict__ q, const __nv_bfloat16* __restrict__ mask, __nv_bfloat16* __restrict__ out,
                 unsigned int* progress, const __grid_constant__ Maps tm) {
    extern __shared__ uint8_t smem_raw[];
    if (threadIdx.x == 0)
        asm volatile("cp.async.bulk.prefetch.L2.global [%0], 32768;" ::"l"(q + (size_t)blockIdx.x * kRows * kD));
    const uint32_t sb = (smem_u32(smem_raw) + 1023u) & ~1023u;
    const uint32_t bar_q = sb + kOffBar;
    const uint32_t bar_empty = bar_q + 8;
    const uint32_t bar_full = bar_empty + 64;
    const uint32_t bar_end = bar_full + 8 * kStages * kSub;
    const uint32_t pace_slot = sb + kOffBar + 448;
    static_assert(kStages <= 8 && kStages * kSub + kEnd <= 32, "barriers");
    const int cta = blockIdx.x;

    if (threadIdx.x == 256) {
        mbar_init(bar_q, 1);
        asm volatile("fence.mbarrier_init.release.cluster;" ::: "memory");
        mbar_expect_tx(bar_q, 32768 + 16384 + 2048);
        tma_load(sb + kOffQ, &tm.q, bar_q, 0, cta * (kRows / 8));
        tma_load(sb + kOffKt, &tm.kt, bar_q, 0, cta * (kT / 8));
        tma_load(sb + kOffVt, &tm.vt, bar_q, 0, cta * (kT / 8));
        asm volatile("cp.async.bulk.shared::cluster.global.mbarrier::complete_tx::bytes [%0], [%1], 2048, [%2];"
                     ::"r"(sb + kOffMask), "l"(mask + (cta / kHkv) * kT * kT), "r"(bar_q) : "memory");
    }
    __syncwarp();
    const int warp = __shfl_sync(0xffffffffu, threadIdx.x >> 5, 0);
    const int lane = threadIdx.x & 31;
    auto put_entry = [&](int x, uint32_t e0, uint32_t e1, uint32_t e2, uint32_t e3) {
        const uint32_t blk = (e0 >> 6) & 7;
        e0 = (e0 & ~24u) | (e0 & 8) << 1 | (e0 & 16) >> 1;
        if (cta & 1) e0 ^= blk == 7 || blk == (7 ^ kOddXor >> 6) ? kOddXorEnd : kOddXor;
        asm volatile("st.shared.v4.u32 [%0], {%1, %2, %3, %4};" ::"r"(sb + kOffTab + 16 * x),
                     "r"(cta * (kC / 8) + e0), "r"(e1), "r"(e2 + sb + kOffRing), "r"(e3) : "memory");
    };

    if (warp >= 8) {
        asm volatile("setmaxnreg.dec.sync.aligned.u32 40;");
        if (warp == 8) {
            asm volatile("barrier.sync 7, 384;" ::: "memory");
            if (elect_one()) {
                uint32_t ta = sb + kOffTab;
#pragma unroll 1
                do {
                    uint32_t e0, e1, e2, e3;
                    asm volatile("ld.shared.v4.u32 {%0, %1, %2, %3}, [%4];" : "=r"(e0), "=r"(e1), "=r"(e2), "=r"(e3) : "r"(ta) : "memory");
                    if ((int)e3 < 0) mbar_wait(bar_empty + ((e3 >> 16) & 0xff), (e3 >> 30) & 1);
                    uint32_t dst = e2 & 0xffffff, bar = bar_full + (e3 & 0xffff), half = e0 >> 31, grp = e0 & 0x7fffffff;
                    const char* map = reinterpret_cast<const char*>(&tm) + (e1 & 0xffff);
                    mbar_expect_tx(bar, (e2 >> 24) << 10);
                    asm volatile("" : "+r"(dst), "+r"(bar), "+r"(half), "+r"(grp), "+l"(map)::"memory");
                    for (int n = 0; n < 0x100000; n++) {
                        uint32_t g, t;
                        asm volatile("ld.volatile.shared.v2.u32 {%0, %1}, [%2];" : "=r"(g), "=r"(t) : "r"(pace_slot) : "memory");
                        if ((int)g + (int)((min((uint32_t)clock() - t, 12000u) * kRateP) >> 16) >= (int)e1 >> 16) break;
                    }
                    tma_load(dst, reinterpret_cast<const CUtensorMap*>(map), bar, half, grp);
                    ta += 16;
                } while (ta < sb + kOffTab + 16 * (kMain + kEnd));
            }
        } else if (warp == 9) {
            uint32_t t_est = clock();
            if (lane == 0) {
                asm volatile("st.shared.v4.u32 [%0], {%1, %2, %3, %3};" ::"r"(pace_slot), "r"(kStartProgress), "r"(t_est), "r"(0) : "memory");
                prefetch_map(&tm.k);
                prefetch_map(&tm.v);
                prefetch_map(&tm.vh64);
                prefetch_map(&tm.vh32);
            }
            __syncwarp();
            asm volatile("barrier.arrive 7, 384;" ::: "memory");
            if (lane == 0) {
                int est = kStartProgress * 256;
                uint32_t g_mark = 0, t_mark = t_est;
                do {
                    uint32_t g, t = clock();
                    asm volatile("ld.relaxed.gpu.global.u32 %0, [%1];" : "=r"(g) : "l"(progress) : "memory");
                    asm volatile("st.volatile.shared.u32 [%0], %1;" ::"r"(pace_slot + 24), "r"(g) : "memory");
                    t += (((uint32_t)clock() - t) * kBeta) >> 8;
                    est += (int)(((t - t_est) * kRateE) >> 8);
                    if (g >= kStartCount) est += (((int)(g << 8) - est) * kWeight) >> 8;
                    t_est = t;
                    if (g - g_mark >= 4 * kCtas) { g_mark = g; t_mark = t; }
                    if (t - t_mark > 60000u) est = kLastNeed * 256;
                    asm volatile("st.volatile.shared.v2.u32 [%0], {%1, %2};" ::"r"(pace_slot), "r"(est >> 8), "r"(t) : "memory");
                } while (est < kLastNeed * 256);
            }
        } else if (warp == 10) {
            asm volatile("barrier.sync 7, 384;" ::: "memory");
            if (lane == 0) {
                Ring r{0, 0};
#pragma unroll 1
                for (int i = 0; i < kItems; i++) {
                    const int y = (i - (kItems - 2)) * kSub + (cta & 3);
                    mbar_wait(y < 0 ? bar_full + 8 * (kSub * r.s + (cta & 3)) : bar_end + 8 * (y + (y == 7)), y < 0 ? r.ph : 0);
                    asm volatile("red.relaxed.gpu.global.inc.u32 [%0], %1;" ::"l"(progress), "n"(kCtas * kItems - 1) : "memory");
                    mbar_arrive(bar_empty + 8 * r.s);
                    r.next();
                }
            }
        } else {
            if (lane < kEnd) {
                const uint32_t of = kEndOffs >> 7 * lane, ky = kEndKeys >> 7 * lane, wn = kEndWins >> 7 * lane;
                constexpr uint32_t kPar = (((kItems - 2) / kStages) & 1) ^ 1;
                static_assert((kItems - 2) / kStages == (kItems - 1) / kStages, "parity");
                put_entry(kMain + lane, (kC / 8 - 32 + 2 * (ky & 15)) | (ky & 64) << 25,
                          (kMain * (kCtas / kSub) + (of & 15) * 16 - 64 - (wn & 127)) << 16 | ((ky >> 4) & 3) * 128,
                          (kEndSlot * kTileBytes + (of & 15) * 4096) | ((of >> 4) & 7) << 26,
                          8 * (kStages * kSub + lane) | 8 * (kEndSlot + (lane >> 2)) << 16 | kPar << 30 | (uint32_t)((lane & ~4) == 0) << 31);
            }
            __syncwarp();
            asm volatile("barrier.arrive 7, 384;" ::: "memory");
        }
    } else {
        if (threadIdx.x < kMain) {
            const int x = threadIdx.x, i = x >> 2, u = x & 3;
            const bool isv = i < 2 * kPairEnd ? (i & 2) != 0 : i > 2 * kPairEnd && !(i & 1);
            const int tile = i < 2 * kPairEnd ? (i >> 2) * 2 + (i & 1) : (isv ? (i >> 1) - 1 : (i + 1) >> 1);
            const int n = i / kStages, s = i - n * kStages;
            put_entry(x, tile * (kTile / 8) + 4 * u, (uint32_t)(x * (kCtas / kSub) - main_window(x)) << 16 | isv * 128,
                      (s * kSub + u) * kSubBytes | 8 << 24,
                      8 * (s * kSub + u) | 8 * s << 16 | (uint32_t)((n & 1) ^ 1) << 30 | (uint32_t)(u == 0) << 31);
        }
        __syncwarp();
        if (elect_one()) {
            mbar_init(bar_empty + 8 * warp, 9);
#pragma unroll
            for (int j = 0; j < 4; j++) mbar_init(bar_full + 8 * (4 * warp + j), 1);
            asm volatile("fence.mbarrier_init.release.cluster;" ::: "memory");
        }
        __syncwarp();
        asm volatile("barrier.sync 7, 384;" ::: "memory");
        asm volatile("setmaxnreg.inc.sync.aligned.u32 232;");
        const int wg = warp >> 2;
        const float kScale = 0.08838834764831845f;
        const float kLog2e = 1.4426950408889634f;
        const float c = kScale * kLog2e;
        if (wg == 1) {
            bar_arrive(1);
            bar_arrive(3);
        }

        const uint64_t dq = make_desc(sb + kOffQ + wg * 16384, 2048);
        float o[64], sc[64];
        uint32_t p[64];
        float l0, l1, a0 = 1.f, a1 = 1.f;
        bool moved = true;
        Ring r{0, 0};
#pragma unroll
        for (int i = 0; i < 64; i++) o[i] = sc[i] = 0.f;
#pragma unroll
        for (int i = 0; i < 32; i++) p[i] = 0;
        float m0, m1;
        mbar_wait(bar_q, 0);
        {
            float st[16];
            const uint64_t dk = make_desc(sb + kOffKt, 2048);
            wg_fence();
#pragma unroll
            for (int k = 0; k < 8; k++) {
                const uint32_t off = ((k >> 2) * 1024 + (k & 3) * 32) >> 4;
                wgmma_qk32(st, dq + off, dk + off, k != 0);
            }
            wg_commit();
            wg_wait<0>();
            fence_regs<0, 16>(st);
#pragma unroll
            for (int i = 0; i < 4; i++) {
#pragma unroll
                for (int h = 0; h < 2; h++) {
                    uint32_t w;
                    asm volatile("ld.shared.u32 %0, [%1];" : "=r"(w)
                                 : "r"(sb + kOffMask + ((warp & 1) * 16 + (lane >> 2) + 8 * h) * 64 + 16 * i + 4 * (lane & 3)));
                    const float ma = __uint_as_float(w << 16), mb = __uint_as_float(w & 0xffff0000u);
                    st[4 * i + 2 * h] = (st[4 * i + 2 * h] * kScale + (1.0f - ma) * -1.0e9f) * kLog2e;
                    st[4 * i + 2 * h + 1] = (st[4 * i + 2 * h + 1] * kScale + (1.0f - mb) * -1.0e9f) * kLog2e;
                }
            }
            m0 = fmaxf(st[0], st[1]);
            m1 = fmaxf(st[2], st[3]);
#pragma unroll
            for (int i = 1; i < 4; i++) {
                m0 = fmaxf(m0, fmaxf(st[4 * i], st[4 * i + 1]));
                m1 = fmaxf(m1, fmaxf(st[4 * i + 2], st[4 * i + 3]));
            }
            m0 = quad_max(m0);
            m1 = quad_max(m1);
            l0 = 0.f;
            l1 = 0.f;
#pragma unroll
            for (int i = 0; i < 4; i++) {
                const float a = ex2(st[4 * i] - m0), b = ex2(st[4 * i + 1] - m0);
                const float e = ex2(st[4 * i + 2] - m1), f = ex2(st[4 * i + 3] - m1);
                l0 += a + b;
                l1 += e + f;
                p[2 * i] = pack_bf16(a, b);
                p[2 * i + 1] = pack_bf16(e, f);
            }
        }
        bool pending = true;
#pragma unroll 1
        for (int kt = 0;;) {
            const bool pv_only = pending && kt > 0 && !(kt & 1) && kt <= kPairEnd;
            const bool tree = kt == 0;
            const bool hand_over = wg == 0 || kt < kTiles - 1;
            if (!pv_only) {
                const uint64_t dk = make_desc(sb + kOffRing + r.s * kTileBytes, 2048);
                mbar_wait(bar_full + 8 * (r.s * kSub), r.ph);
                mbar_wait(bar_full + 8 * (r.s * kSub + 1), r.ph);
                wg_fence();
#pragma unroll
                for (int k = 0; k < 8; k++) {
                    const uint32_t off = ((k >> 2) * 1024 + (k & 3) * 32) >> 4;
                    wgmma_qk64<0>(sc, dq + off, dk + off, k != 0);
                }
                wg_commit();
                mbar_wait(bar_full + 8 * (r.s * kSub + 2), r.ph);
                mbar_wait(bar_full + 8 * (r.s * kSub + 3), r.ph);
                bar_sync(1 + wg);
                wg_fence();
#pragma unroll
                for (int k = 0; k < 8; k++) {
                    const uint32_t off = ((k >> 2) * 1024 + (k & 3) * 32) >> 4;
                    wgmma_qk64<32>(sc, dq + off, dk + (16384 >> 4) + off, k != 0);
                }
                wg_commit();
                if (hand_over) bar_arrive(2 - wg);
                wg_wait<1>();
                fence_regs<0, 32>(sc);
                float x0 = fmaxf(sc[0], sc[1]), x1 = fmaxf(sc[2], sc[3]);
#pragma unroll
                for (int i = 1; i < 8; i++) {
                    x0 = fmaxf(x0, fmaxf(sc[4 * i], sc[4 * i + 1]));
                    x1 = fmaxf(x1, fmaxf(sc[4 * i + 2], sc[4 * i + 3]));
                }
                asm volatile("" : "+f"(x0), "+f"(x1)::"memory");
                wg_wait<0>();
                fence_regs<32, 64>(sc);
                if (lane == 0) mbar_arrive(bar_empty + 8 * r.s);
                r.next();

#pragma unroll
                for (int i = 8; i < 16; i++) {
                    x0 = fmaxf(x0, fmaxf(sc[4 * i], sc[4 * i + 1]));
                    x1 = fmaxf(x1, fmaxf(sc[4 * i + 2], sc[4 * i + 3]));
                }
                float n0 = fmaxf(m0, quad_max(x0) * c), n1 = fmaxf(m1, quad_max(x1) * c);
                moved = __any_sync(0xffffffffu, n0 > m0 || n1 > m1);
                {
                    float z;
                    asm volatile("st.volatile.shared.f32 [%2 + 4], %3;\n"
                                 "barrier.sync %1, 256;\nld.volatile.shared.f32 %0, [%2];"
                                 : "=f"(z) : "r"(3 + wg), "r"(pace_slot + 12), "f"(n0 + n1) : "memory");
                    n0 += z;
                    n1 += z;
                }
                a0 = ex2(m0 - n0);
                a1 = ex2(m1 - n1);
                m0 = n0;
                m1 = n1;
                l0 *= a0;
                l1 *= a1;
#pragma unroll
                for (int i = 0; i < 16; i++) {
                    sc[4 * i] = ex2(fmaf(sc[4 * i], c, -n0));
                    sc[4 * i + 1] = ex2(fmaf(sc[4 * i + 1], c, -n0));
                    sc[4 * i + 2] = ex2(fmaf(sc[4 * i + 2], c, -n1));
                    sc[4 * i + 3] = ex2(fmaf(sc[4 * i + 3], c, -n1));
                    l0 += sc[4 * i] + sc[4 * i + 1];
                    l1 += sc[4 * i + 2] + sc[4 * i + 3];
                }
                {
                    asm volatile("st.volatile.shared.f32 [%0], %1;" ::"r"(pace_slot + 16), "f"(sc[59]) : "memory");
                    if (hand_over) bar_arrive(4 - wg);
                }
                if (++kt == kTiles) break;
            }

            if (pending) {
                const uint32_t vslot = sb + kOffRing + r.s * kTileBytes;
                const uint32_t vbar = bar_full + 8 * (r.s * kSub);
                if (!tree) mbar_wait(vbar, r.ph);
                pv_piece(o, p, tree ? sb + kOffVt : vslot);
                if (!tree) {
#pragma unroll
                    for (int u = 1; u < 4; u++) {
                        mbar_wait(vbar + 8 * u, r.ph);
                        pv_piece(o, p + 8 * u, vslot + u * kSubBytes);
                    }
                }
            }
            wg_wait<0>();
            fence_regs<0, 64>(o);
            if (pending && !tree) {
                if (lane == 0) mbar_arrive(bar_empty + 8 * r.s);
                r.next();
            }
            pending = !pv_only;
            if (!pv_only) {
                if (moved) {
#pragma unroll
                    for (int i = 0; i < 16; i++) {
                        o[4 * i] *= a0;
                        o[4 * i + 1] *= a0;
                        o[4 * i + 2] *= a1;
                        o[4 * i + 3] *= a1;
                    }
                }
#pragma unroll
                for (int i = 0; i < 16; i++) {
                    p[2 * i] = pack_bf16(sc[4 * i], sc[4 * i + 1]);
                    p[2 * i + 1] = pack_bf16(sc[4 * i + 2], sc[4 * i + 3]);
                }
            }
        }

#pragma unroll
        for (int h = 0; h < 2; h++) {
            const float a = h ? a1 : a0;
            if (__any_sync(0xffffffffu, a != 1.f)) {
                const uint32_t hi = pack_bf16(a, a);
                const float rest = a - __uint_as_float(hi << 16);
                const uint32_t lo = pack_bf16(rest, rest);
#pragma unroll
                for (int i = 0; i < 16; i++) {
                    o[4 * i + 2 * h] *= a;
                    o[4 * i + 2 * h + 1] *= a;
                    asm("{\n.reg .b32 t;\nmul.rn.bf16x2 t, %0, %2;\nfma.rn.bf16x2 %0, %0, %1, t;\n}" : "+r"(p[2 * i + h]) : "r"(hi), "r"(lo));
                }
            }
        }
        float i0, i1;
        const uint32_t stg = sb + kOffQ + warp * 4096;
        const uint32_t swz = ((lane >> 3) ^ (lane & 7)) << 4;
        uint32_t sa = stg + (lane & 7) * 128 + swz, sa2 = sa ^ 64;
        uint32_t la = stg + (lane >> 3) * 128 + swz, la2 = (la ^ 64) + 512;
        uint4* gp = reinterpret_cast<uint4*>(out + (size_t)(cta * kRows + warp * 16 + (lane >> 3)) * kD) + (lane & 7);
        asm volatile("" : "+r"(sa), "+r"(sa2), "+r"(la), "+r"(la2), "+l"(gp));
        uint4 vv[4] = {};
        auto put = [&](int j, int h) {
            asm volatile("st.global.v4.u32 [%0], {%1, %2, %3, %4};"
                         ::"l"(gp + 64 * j + 8 * h), "r"(vv[j].x), "r"(vv[j].y), "r"(vv[j].z), "r"(vv[j].w) : "memory");
        };
        auto store_half = [&](auto hc) {
            constexpr int h = decltype(hc)::value;
#pragma unroll
            for (int hr = 0; hr < 2; hr++) {
                const float f = hr ? i1 : i0;
#pragma unroll
                for (int i = 0; i < 2; i++) {
                    const float* v = o + 32 * h + 16 * i + 2 * hr;
                    asm volatile("stmatrix.sync.aligned.m8n8.x4.shared.b16 [%0], {%1, %2, %3, %4};"
                                 ::"r"((i ? sa2 : sa) + hr * 1024 + h * 2048), "r"(pack_bf16(v[0] * f, v[1] * f)),
                                   "r"(pack_bf16(v[4] * f, v[5] * f)), "r"(pack_bf16(v[8] * f, v[9] * f)),
                                   "r"(pack_bf16(v[12] * f, v[13] * f)) : "memory");
                }
                __syncwarp();
                uint4* v = vv + 2 * hr;
#pragma unroll
                for (int i = 0; i < 2; i++)
                    asm volatile("ld.volatile.shared.v4.u32 {%0, %1, %2, %3}, [%4];" : "=r"(v[i].x), "=r"(v[i].y), "=r"(v[i].z), "=r"(v[i].w)
                                 : "r"((i ? la2 : la) + hr * 1024 + h * 2048) : "memory");
                if (h || !hr) {
                    put(2 * hr, h);
                    put(2 * hr + 1, h);
                }
            }
        };
        auto pack_last = [&]() {
            i0 = rcp(quad_sum(l0));
            i1 = rcp(quad_sum(l1));
#pragma unroll
            for (int i = 0; i < 16; i++) {
                p[32 + 2 * i] = pack_bf16(sc[4 * i], sc[4 * i + 1]);
                p[32 + 2 * i + 1] = pack_bf16(sc[4 * i + 2], sc[4 * i + 3]);
            }
#pragma unroll
            for (int i = 32; i < 64; i++) asm volatile("" : "+r"(p[i])::"memory");
            asm volatile("" : "+f"(i0), "+f"(i1)::"memory");
        };
        const uint64_t dend = make_desc(sb + kOffRing + kEndSlot * kTileBytes, 1024);
        static_for<kEnd>([&](auto yc) {
            constexpr int y = yc.value;
            constexpr EndPiece e = end_piece(y);
            constexpr int step = e.kind == F ? 4096 : 2048;
            const uint64_t dv = dend + (end_offset(y) >> 4) + (e.kind == F ? (uint64_t)(1024 >> 4) << 32 : 0);
            mbar_wait(bar_end + 8 * y, 0);
            wg_fence();
            if (e.kind != R) {
#pragma unroll
                for (int k = 0; k < e.nk; k++) wgmma_pv64<0>(o, p + 4 * (e.k0 + k), dv + ((k * step) >> 4));
                wg_commit();
            }
            if (e.kind != L) {
#pragma unroll
                for (int k = 0; k < e.nk; k++) wgmma_pv64<32>(o, p + 4 * (e.k0 + k), dv + ((k * step + (e.kind == F ? 1024 : 0)) >> 4));
                wg_commit();
            }
            if (y == 0) pack_last();
            if (y == kEndLeft + 1) {
                put(2, 0);
                put(3, 0);
            }
            if (y == kEndLeft) {
                wg_wait<1>();
                fence_regs<0, 32>(o);
                store_half(IntC<0>{});
            }
        });
        wg_wait<0>();
        fence_regs<32, 64>(o);
        store_half(IntC<1>{});
    }
}

typedef CUresult (*EncodeFn)(CUtensorMap*, CUtensorMapDataType, cuuint32_t, void*, const cuuint64_t*,
                             const cuuint64_t*, const cuuint32_t*, const cuuint32_t*, CUtensorMapInterleave,
                             CUtensorMapSwizzle, CUtensorMapL2promotion, CUtensorMapFloatOOBfill);

void make_map(EncodeFn enc, CUtensorMap* m, const void* p, uint64_t rows, uint32_t box_rows, uint32_t halves) {
    const cuuint64_t dims[4] = {64, 8, 2, rows / 8};
    const cuuint64_t strides[3] = {256, 128, 2048};
    const cuuint32_t box[4] = {64, 8, halves, box_rows / 8};
    const cuuint32_t es[4] = {1, 1, 1, 1};
    enc(m, CU_TENSOR_MAP_DATA_TYPE_BFLOAT16, 4, const_cast<void*>(p), dims, strides, box, es,
        CU_TENSOR_MAP_INTERLEAVE_NONE, CU_TENSOR_MAP_SWIZZLE_128B,
        halves == 2 ? CU_TENSOR_MAP_L2_PROMOTION_L2_256B : CU_TENSOR_MAP_L2_PROMOTION_L2_128B,
        CU_TENSOR_MAP_FLOAT_OOB_FILL_NONE);
}

}

extern "C" void kernel_launch(void* const* d_in, const int* in_sizes, int n_in, void* d_out, int out_size) {
    (void)in_sizes; (void)n_in; (void)out_size;
    static EncodeFn enc = nullptr;
    static unsigned int* progress = nullptr;
    if (!enc) {
        cudaDriverEntryPointQueryResult qr;
        cudaGetDriverEntryPoint("cuTensorMapEncodeTiled", (void**)&enc, cudaEnableDefault, &qr);
        cudaFuncSetAttribute(tree_attn_kernel, cudaFuncAttributeMaxDynamicSharedMemorySize, kSmemBytes);
        cudaGetSymbolAddress((void**)&progress, g_progress);
    }
    Maps tm;
    make_map(enc, &tm.q, d_in[0], (uint64_t)kCtas * kRows, kRows, 2);
    make_map(enc, &tm.k, d_in[1], (uint64_t)kCtas * kC, 32, 2);
    make_map(enc, &tm.v, d_in[2], (uint64_t)kCtas * kC, 32, 2);
    make_map(enc, &tm.vh64, d_in[2], (uint64_t)kCtas * kC, 64, 1);
    make_map(enc, &tm.vh32, d_in[2], (uint64_t)kCtas * kC, 32, 1);
    make_map(enc, &tm.kt, d_in[3], (uint64_t)kCtas * kT, kT, 2);
    make_map(enc, &tm.vt, d_in[4], (uint64_t)kCtas * kT, kT, 2);
    tree_attn_kernel<<<kCtas, kThreads, kSmemBytes, cudaStreamPerThread>>>(
        (const __nv_bfloat16*)d_in[0], (const __nv_bfloat16*)d_in[5], (__nv_bfloat16*)d_out, progress, tm);
}
```

```cpp
#include <cuda_runtime.h>
#include <cuda_bf16.h>
#include <cuda.h>
#include <stddef.h>
#include <stdint.h>

namespace {

constexpr int kB = 16, kHq = 32, kHkv = 8, kT = 32, kC = 4096, kD = 128;
constexpr int kCtas = kB * kHkv;
constexpr int kRows = (kHq / kHkv) * kT;
constexpr int kTile = 128;
constexpr int kTiles = kC / kTile;
constexpr int kItems = 2 * kTiles;
constexpr int kTileBytes = kTile * kD * 2;
constexpr int kStages = 5;
constexpr int kSub = 4;
constexpr int kSubBytes = kTileBytes / kSub;
constexpr int kPairEnd = 28;
constexpr uint32_t kOddXor = 348, kOddXorEnd = 56;

enum { L, F, R };
struct EndPiece { int kind, k0, nk, window; };
constexpr int kEnd = 9;
__host__ __device__ constexpr EndPiece end_piece(int y) {
    constexpr EndPiece e[kEnd] = {{L, 0, 4, 124}, {L, 4, 4, 131}, {F, 8, 2, 131}, {F, 10, 2, 129}, {F, 12, 2, 116},
                                  {F, 14, 2, 116}, {R, 0, 4, 114}, {R, 4, 2, 120}, {R, 6, 2, 151}};
    return e[y];
}
constexpr int kEndLeft = 5;
__host__ __device__ constexpr int end_offset(int y) {
    int o = 0;
    for (int j = 0; j < y; j++) o += end_piece(j).nk * (end_piece(j).kind == F ? 4096 : 2048);
    return o;
}
constexpr int kMain = (kItems - 2) * kSub;
constexpr int kEndSlot = (kItems - 2) % kStages;
static_assert(end_offset(kEnd) == 2 * kTileBytes && end_offset(4) == kTileBytes && kEndSlot + 1 < kStages, "end pieces");

__device__ __forceinline__ int main_window(int x) { return min(240, 136 + max((kMain - x) * 9 / 4, (kMain - x) * 5 - 66)); }
constexpr int kStartProgress = -260;
constexpr uint32_t kStartCount = 384;
constexpr uint32_t kRateP = 2750, kRateE = 3470;
constexpr uint32_t kBeta = 37;
constexpr int kWeight = 126;

constexpr int kOffQ = 0;
constexpr int kOffKt = 32768;
constexpr int kOffVt = kOffKt + 8192;
constexpr int kOffMask = kOffVt + 8192;
constexpr int kOffRing = kOffMask + 2048;
constexpr int kOffBar = kOffRing + kStages * kTileBytes;
constexpr int kOffTab = kOffBar + 512;
constexpr int kSmemBytes = kOffTab + 16 * (kMain + kEnd) + 1024;
constexpr int kThreads = 384;

__device__ unsigned int g_progress;

struct Maps { CUtensorMap k, v, vh64, vh32, q, kt, vt; };

__device__ __forceinline__ uint32_t smem_u32(const void* p) { return (uint32_t)__cvta_generic_to_shared(p); }

__device__ __forceinline__ void mbar_init(uint32_t bar, uint32_t cnt) {
    asm volatile("mbarrier.init.shared::cta.b64 [%0], %1;" ::"r"(bar), "r"(cnt) : "memory");
}
__device__ __forceinline__ void mbar_expect_tx(uint32_t bar, uint32_t bytes) {
    asm volatile("mbarrier.arrive.expect_tx.shared::cta.b64 _, [%0], %1;" ::"r"(bar), "r"(bytes) : "memory");
}
__device__ __forceinline__ void mbar_arrive(uint32_t bar) {
    asm volatile("mbarrier.arrive.shared::cta.b64 _, [%0];" ::"r"(bar) : "memory");
}
__device__ __forceinline__ void mbar_wait(uint32_t bar, uint32_t parity) {
    asm volatile(
        "{\n.reg .pred p, q;\n.reg .u32 n;\nmov.u32 n, 0;\n"
        "WAIT_%=:\n"
        "mbarrier.try_wait.parity.shared::cta.b64 p, [%0], %1;\n"
        "add.u32 n, n, 1;\n"
        "setp.lt.and.u32 q, n, %2, !p;\n"
        "@q bra WAIT_%=;\n}"
        ::"r"(bar), "r"(parity), "n"(0x20000) : "memory");
}

__device__ __forceinline__ void tma_load(uint32_t dst, const CUtensorMap* m, uint32_t bar, int half, int grp) {
    asm volatile(
        "cp.async.bulk.tensor.4d.shared::cluster.global.mbarrier::complete_tx::bytes [%0], [%1, {%3, %3, %4, %5}], [%2];"
        ::"r"(dst), "l"(m), "r"(bar), "r"(0), "r"(half), "r"(grp) : "memory");
}
__device__ __forceinline__ void tma_load_stream(uint32_t dst, const void* m, uint32_t bar, int half, int grp, uint64_t pol) {
    asm volatile(
        "cp.async.bulk.tensor.4d.shared::cluster.global.mbarrier::complete_tx::bytes.L2::cache_hint [%0], [%1, {%3, %3, %4, %5}], [%2], %6;"
        ::"r"(dst), "l"(m), "r"(bar), "r"(0), "r"(half), "r"(grp), "l"(pol) : "memory");
}
__device__ __forceinline__ bool elect_one() {
    uint32_t p;
    asm volatile("{\n.reg .pred p;\nelect.sync _|p, 0xffffffff;\nselp.u32 %0, 1, 0, p;\n}" : "=r"(p));
    return p != 0;
}
__device__ __forceinline__ void prefetch_map(const CUtensorMap* m) {
    asm volatile("prefetch.tensormap [%0];" ::"l"(m) : "memory");
}

__device__ __forceinline__ uint64_t make_desc(uint32_t addr, uint32_t sbo) {
    return (uint64_t)((addr & 0x3FFFF) >> 4) | (1ull << 16) | ((uint64_t)(sbo >> 4) << 32) | (1ull << 62);
}

__device__ __forceinline__ void wg_fence() { asm volatile("wgmma.fence.sync.aligned;" ::: "memory"); }
__device__ __forceinline__ void wg_commit() { asm volatile("wgmma.commit_group.sync.aligned;" ::: "memory"); }
template <int N> __device__ __forceinline__ void wg_wait() { asm volatile("wgmma.wait_group.sync.aligned %0;" ::"n"(N) : "memory"); }
template <int LO, int HI, int N> __device__ __forceinline__ void fence_regs(float (&r)[N]) {
#pragma unroll
    for (int i = LO; i < HI; i++) asm volatile("" : "+f"(r[i])::"memory");
}
__device__ __forceinline__ void bar_sync(int id) { asm volatile("barrier.sync %0, 256;" ::"r"(id) : "memory"); }
__device__ __forceinline__ void bar_arrive(int id) { asm volatile("barrier.arrive %0, 256;" ::"r"(id) : "memory"); }

#define ACC8(d, o) "+f"(d[o]), "+f"(d[o + 1]), "+f"(d[o + 2]), "+f"(d[o + 3]), "+f"(d[o + 4]), "+f"(d[o + 5]), "+f"(d[o + 6]), "+f"(d[o + 7])
#define ACC32(d, o) ACC8(d, o), ACC8(d, o + 8), ACC8(d, o + 16), ACC8(d, o + 24)
#define REGS32                                                                \
    "{%0, %1, %2, %3, %4, %5, %6, %7, %8, %9, %10, %11, %12, %13, %14, %15, " \
    "%16, %17, %18, %19, %20, %21, %22, %23, %24, %25, %26, %27, %28, %29, %30, %31}"

template <int O>
__device__ __forceinline__ void wgmma_qk64(float (&d)[64], uint64_t da, uint64_t db, int acc) {
    asm volatile(
        "{\n.reg .pred p;\nsetp.ne.b32 p, %34, 0;\n"
        "wgmma.mma_async.sync.aligned.m64n64k16.f32.bf16.bf16 " REGS32 ", %32, %33, p, 1, 1, 0, 0;\n}"
        : ACC32(d, O) : "l"(da), "l"(db), "r"(acc));
}
__device__ __forceinline__ void wgmma_qk32(float (&d)[16], uint64_t da, uint64_t db, int acc) {
    asm volatile(
        "{\n.reg .pred p;\nsetp.ne.b32 p, %18, 0;\n"
        "wgmma.mma_async.sync.aligned.m64n32k16.f32.bf16.bf16 "
        "{%0, %1, %2, %3, %4, %5, %6, %7, %8, %9, %10, %11, %12, %13, %14, %15}, %16, %17, p, 1, 1, 0, 0;\n}"
        : ACC8(d, 0), ACC8(d, 8) : "l"(da), "l"(db), "r"(acc));
}
template <int O>
__device__ __forceinline__ void wgmma_pv64(float (&d)[64], const uint32_t* a, uint64_t db) {
    asm volatile(
        "{\n.reg .pred p;\nsetp.ne.b32 p, 1, 0;\n"
        "wgmma.mma_async.sync.aligned.m64n64k16.f32.bf16.bf16 " REGS32 ", {%32, %33, %34, %35}, %36, p, 1, 1, 1;\n}"
        : ACC32(d, O) : "r"(a[0]), "r"(a[1]), "r"(a[2]), "r"(a[3]), "l"(db));
}
__device__ __forceinline__ void pv_piece(float (&o)[64], const uint32_t* a, uint32_t addr) {
    const uint64_t dv = make_desc(addr, 2048);
    wg_fence();
    wgmma_pv64<0>(o, a, dv);
    wgmma_pv64<0>(o, a + 4, dv + (4096 >> 4));
    wg_commit();
    wgmma_pv64<32>(o, a, dv + (1024 >> 4));
    wgmma_pv64<32>(o, a + 4, dv + (5120 >> 4));
    wg_commit();
}

__device__ __forceinline__ float ex2(float x) {
    float y;
    asm("ex2.approx.ftz.f32 %0, %1;" : "=f"(y) : "f"(x));
    return y;
}
__device__ __forceinline__ float rcp(float x) {
    float y;
    asm("rcp.approx.ftz.f32 %0, %1;" : "=f"(y) : "f"(x));
    return y;
}
__device__ __forceinline__ uint32_t pack_bf16(float lo, float hi) {
    uint32_t r;
    asm("cvt.rn.bf16x2.f32 %0, %1, %2;" : "=r"(r) : "f"(hi), "f"(lo));
    return r;
}
__device__ __forceinline__ float quad_max(float x) {
    x = fmaxf(x, __shfl_xor_sync(0xffffffffu, x, 1));
    return fmaxf(x, __shfl_xor_sync(0xffffffffu, x, 2));
}
__device__ __forceinline__ float quad_sum(float x) {
    x += __shfl_xor_sync(0xffffffffu, x, 1);
    return x + __shfl_xor_sync(0xffffffffu, x, 2);
}

template <int V> struct IntC { static constexpr int value = V; };
template <int N, int I = 0, class Fn> __device__ __forceinline__ void static_for(Fn fn) {
    if constexpr (I < N) {
        fn(IntC<I>{});
        static_for<N, I + 1>(fn);
    }
}
constexpr uint64_t end_field(int f) {
    uint64_t m = 0;
    for (int y = 0; y < kEnd; y++) {
        const EndPiece e = end_piece(y);
        m |= (uint64_t)(f == 0 ? end_offset(y) / 4096 | (end_offset(y + 1) - end_offset(y)) / 4096 << 4
                        : f == 1 ? e.k0 | (e.kind == F ? 1 : e.nk == 4 ? 2 : 3) << 4 | (e.kind == R) << 6
                        : e.window - 64) << 7 * y;
    }
    return m;
}
constexpr uint64_t kEndOffs = end_field(0), kEndKeys = end_field(1), kEndWins = end_field(2);
constexpr int last_need() {
    int m = 0;
    for (int y = 0; y < kEnd; y++) {
        const int need = kMain * (kCtas / kSub) + end_offset(y) / 256 - end_piece(y).window;
        m = need > m ? need : m;
    }
    return m;
}
constexpr int kLastNeed = last_need();
struct Ring {
    int s;
    uint32_t ph;
    __device__ __forceinline__ void next() { if (++s == kStages) { s = 0; ph ^= 1; } }
};

__global__ void __launch_bounds__(kThreads, 1)
tree_attn_kernel(const __nv_bfloat16* __restrict__ q, const __nv_bfloat16* __restrict__ mask, __nv_bfloat16* __restrict__ out,
                 unsigned int* progress, const __grid_constant__ Maps tm) {
    extern __shared__ uint8_t smem_raw[];
    if (threadIdx.x == 0)
        asm volatile("cp.async.bulk.prefetch.L2.global [%0], 32768;" ::"l"(q + (size_t)blockIdx.x * kRows * kD));
    const uint32_t sb = (smem_u32(smem_raw) + 1023u) & ~1023u;
    const uint32_t bar_q = sb + kOffBar;
    const uint32_t bar_empty = bar_q + 8;
    const uint32_t bar_full = bar_empty + 64;
    const uint32_t bar_end = bar_full + 8 * kStages * kSub;
    const uint32_t pace_slot = sb + kOffBar + 448;
    static_assert(kStages <= 8 && kStages * kSub + kEnd <= 32, "barriers");
    const int cta = blockIdx.x;

    if (threadIdx.x == 256) {
        mbar_init(bar_q, 1);
        asm volatile("fence.mbarrier_init.release.cluster;" ::: "memory");
        mbar_expect_tx(bar_q, 32768 + 16384 + 2048);
        tma_load(sb + kOffQ, &tm.q, bar_q, 0, cta * (kRows / 8));
        tma_load(sb + kOffKt, &tm.kt, bar_q, 0, cta * (kT / 8));
        tma_load(sb + kOffVt, &tm.vt, bar_q, 0, cta * (kT / 8));
        asm volatile("cp.async.bulk.shared::cluster.global.mbarrier::complete_tx::bytes [%0], [%1], 2048, [%2];"
                     ::"r"(sb + kOffMask), "l"(mask + (cta / kHkv) * kT * kT), "r"(bar_q) : "memory");
    }
    __syncwarp();
    const int warp = __shfl_sync(0xffffffffu, threadIdx.x >> 5, 0);
    const int lane = threadIdx.x & 31;
    auto put_entry = [&](int x, uint32_t e0, uint32_t e1, uint32_t e2, uint32_t e3) {
        const uint32_t blk = (e0 >> 6) & 7;
        e0 = (e0 & ~24u) | (e0 & 8) << 1 | (e0 & 16) >> 1;
        if (cta & 1) e0 ^= blk == 7 || blk == (7 ^ kOddXor >> 6) ? kOddXorEnd : kOddXor;
        asm volatile("st.shared.v4.u32 [%0], {%1, %2, %3, %4};" ::"r"(sb + kOffTab + 16 * x),
                     "r"(cta * (kC / 8) + e0), "r"(e1), "r"(e2 + sb + kOffRing), "r"(e3) : "memory");
    };

    if (warp >= 8) {
        asm volatile("setmaxnreg.dec.sync.aligned.u32 40;");
        if (warp == 8) {
            asm volatile("barrier.sync 7, 384;" ::: "memory");
            if (elect_one()) {
                uint32_t ta = sb + kOffTab;
                uint64_t pol;
                asm volatile("createpolicy.fractional.L2::evict_first.b64 %0, 1.0;" : "=l"(pol));
#pragma unroll 1
                do {
                    uint32_t e0, e1, e2, e3;
                    asm volatile("ld.shared.v4.u32 {%0, %1, %2, %3}, [%4];" : "=r"(e0), "=r"(e1), "=r"(e2), "=r"(e3) : "r"(ta) : "memory");
                    if ((int)e3 < 0) mbar_wait(bar_empty + ((e3 >> 16) & 0xff), (e3 >> 30) & 1);
                    uint32_t dst = e2 & 0xffffff, bar = bar_full + (e3 & 0xffff), half = e0 >> 31, grp = e0 & 0x7fffffff;
                    const char* map = reinterpret_cast<const char*>(&tm) + (e1 & 0xffff);
                    mbar_expect_tx(bar, (e2 >> 24) << 10);
                    asm volatile("" : "+r"(dst), "+r"(bar), "+r"(half), "+r"(grp), "+l"(map)::"memory");
                    for (int n = 0; n < 0x100000; n++) {
                        uint32_t g, t;
                        asm volatile("ld.volatile.shared.v2.u32 {%0, %1}, [%2];" : "=r"(g), "=r"(t) : "r"(pace_slot) : "memory");
                        if ((int)g + (int)((min((uint32_t)clock() - t, 12000u) * kRateP) >> 16) >= (int)e1 >> 16) break;
                    }
                    tma_load_stream(dst, map, bar, half, grp, pol);
                    ta += 16;
                } while (ta < sb + kOffTab + 16 * (kMain + kEnd));
            }
        } else if (warp == 9) {
            uint32_t t_est = clock();
            if (lane == 0) {
                asm volatile("st.shared.v4.u32 [%0], {%1, %2, %3, %3};" ::"r"(pace_slot), "r"(kStartProgress), "r"(t_est), "r"(0) : "memory");
                prefetch_map(&tm.k);
                prefetch_map(&tm.v);
                prefetch_map(&tm.vh64);
                prefetch_map(&tm.vh32);
            }
            __syncwarp();
            asm volatile("barrier.arrive 7, 384;" ::: "memory");
            if (lane == 0) {
                int est = kStartProgress * 256;
                uint32_t g_mark = 0, t_mark = t_est;
                do {
                    uint32_t g, t = clock();
                    asm volatile("ld.relaxed.gpu.global.u32 %0, [%1];" : "=r"(g) : "l"(progress) : "memory");
                    asm volatile("st.volatile.shared.u32 [%0], %1;" ::"r"(pace_slot + 24), "r"(g) : "memory");
                    t += (((uint32_t)clock() - t) * kBeta) >> 8;
                    est += (int)(((t - t_est) * kRateE) >> 8);
                    if (g >= kStartCount) est += (((int)(g << 8) - est) * kWeight) >> 8;
                    t_est = t;
                    if (g - g_mark >= 4 * kCtas) { g_mark = g; t_mark = t; }
                    if (t - t_mark > 60000u) est = kLastNeed * 256;
                    asm volatile("st.volatile.shared.v2.u32 [%0], {%1, %2};" ::"r"(pace_slot), "r"(est >> 8), "r"(t) : "memory");
                } while (est < kLastNeed * 256);
            }
        } else if (warp == 10) {
            asm volatile("barrier.sync 7, 384;" ::: "memory");
            if (lane == 0) {
                Ring r{0, 0};
#pragma unroll 1
                for (int i = 0; i < kItems; i++) {
                    const int y = (i - (kItems - 2)) * kSub + (cta & 3);
                    mbar_wait(y < 0 ? bar_full + 8 * (kSub * r.s + (cta & 3)) : bar_end + 8 * (y + (y == 7)), y < 0 ? r.ph : 0);
                    asm volatile("red.relaxed.gpu.global.inc.u32 [%0], %1;" ::"l"(progress), "n"(kCtas * kItems - 1) : "memory");
                    mbar_arrive(bar_empty + 8 * r.s);
                    r.next();
                }
            }
        } else {
            if (lane < kEnd) {
                const uint32_t of = kEndOffs >> 7 * lane, ky = kEndKeys >> 7 * lane, wn = kEndWins >> 7 * lane;
                constexpr uint32_t kPar = (((kItems - 2) / kStages) & 1) ^ 1;
                static_assert((kItems - 2) / kStages == (kItems - 1) / kStages, "parity");
                put_entry(kMain + lane, (kC / 8 - 32 + 2 * (ky & 15)) | (ky & 64) << 25,
                          (kMain * (kCtas / kSub) + (of & 15) * 16 - 64 - (wn & 127)) << 16 | ((ky >> 4) & 3) * 128,
                          (kEndSlot * kTileBytes + (of & 15) * 4096) | ((of >> 4) & 7) << 26,
                          8 * (kStages * kSub + lane) | 8 * (kEndSlot + (lane >> 2)) << 16 | kPar << 30 | (uint32_t)((lane & ~4) == 0) << 31);
            }
            __syncwarp();
            asm volatile("barrier.arrive 7, 384;" ::: "memory");
        }
    } else {
        if (threadIdx.x < kMain) {
            const int x = threadIdx.x, i = x >> 2, u = x & 3;
            const bool isv = i < 2 * kPairEnd ? (i & 2) != 0 : i > 2 * kPairEnd && !(i & 1);
            const int tile = i < 2 * kPairEnd ? (i >> 2) * 2 + (i & 1) : (isv ? (i >> 1) - 1 : (i + 1) >> 1);
            const int n = i / kStages, s = i - n * kStages;
            put_entry(x, tile * (kTile / 8) + 4 * u, (uint32_t)(x * (kCtas / kSub) - main_window(x)) << 16 | isv * 128,
                      (s * kSub + u) * kSubBytes | 8 << 24,
                      8 * (s * kSub + u) | 8 * s << 16 | (uint32_t)((n & 1) ^ 1) << 30 | (uint32_t)(u == 0) << 31);
        }
        __syncwarp();
        if (elect_one()) {
            mbar_init(bar_empty + 8 * warp, 9);
#pragma unroll
            for (int j = 0; j < 4; j++) mbar_init(bar_full + 8 * (4 * warp + j), 1);
            asm volatile("fence.mbarrier_init.release.cluster;" ::: "memory");
        }
        __syncwarp();
        asm volatile("barrier.sync 7, 384;" ::: "memory");
        asm volatile("setmaxnreg.inc.sync.aligned.u32 232;");
        const int wg = warp >> 2;
        const float kScale = 0.08838834764831845f;
        const float kLog2e = 1.4426950408889634f;
        const float c = kScale * kLog2e;
        if (wg == 1) {
            bar_arrive(1);
            bar_arrive(3);
        }

        const uint64_t dq = make_desc(sb + kOffQ + wg * 16384, 2048);
        float o[64], sc[64];
        uint32_t p[64];
        float l0, l1, a0 = 1.f, a1 = 1.f;
        bool moved = true;
        Ring r{0, 0};
#pragma unroll
        for (int i = 0; i < 64; i++) o[i] = sc[i] = 0.f;
#pragma unroll
        for (int i = 0; i < 32; i++) p[i] = 0;
        float m0, m1;
        mbar_wait(bar_q, 0);
        {
            float st[16];
            const uint64_t dk = make_desc(sb + kOffKt, 2048);
            wg_fence();
#pragma unroll
            for (int k = 0; k < 8; k++) {
                const uint32_t off = ((k >> 2) * 1024 + (k & 3) * 32) >> 4;
                wgmma_qk32(st, dq + off, dk + off, k != 0);
            }
            wg_commit();
            wg_wait<0>();
            fence_regs<0, 16>(st);
#pragma unroll
            for (int i = 0; i < 4; i++) {
#pragma unroll
                for (int h = 0; h < 2; h++) {
                    uint32_t w;
                    asm volatile("ld.shared.u32 %0, [%1];" : "=r"(w)
                                 : "r"(sb + kOffMask + ((warp & 1) * 16 + (lane >> 2) + 8 * h) * 64 + 16 * i + 4 * (lane & 3)));
                    const float ma = __uint_as_float(w << 16), mb = __uint_as_float(w & 0xffff0000u);
                    st[4 * i + 2 * h] = (st[4 * i + 2 * h] * kScale + (1.0f - ma) * -1.0e9f) * kLog2e;
                    st[4 * i + 2 * h + 1] = (st[4 * i + 2 * h + 1] * kScale + (1.0f - mb) * -1.0e9f) * kLog2e;
                }
            }
            m0 = fmaxf(st[0], st[1]);
            m1 = fmaxf(st[2], st[3]);
#pragma unroll
            for (int i = 1; i < 4; i++) {
                m0 = fmaxf(m0, fmaxf(st[4 * i], st[4 * i + 1]));
                m1 = fmaxf(m1, fmaxf(st[4 * i + 2], st[4 * i + 3]));
            }
            m0 = quad_max(m0);
            m1 = quad_max(m1);
            l0 = 0.f;
            l1 = 0.f;
#pragma unroll
            for (int i = 0; i < 4; i++) {
                const float a = ex2(st[4 * i] - m0), b = ex2(st[4 * i + 1] - m0);
                const float e = ex2(st[4 * i + 2] - m1), f = ex2(st[4 * i + 3] - m1);
                l0 += a + b;
                l1 += e + f;
                p[2 * i] = pack_bf16(a, b);
                p[2 * i + 1] = pack_bf16(e, f);
            }
        }
        bool pending = true;
#pragma unroll 1
        for (int kt = 0;;) {
            const bool pv_only = pending && kt > 0 && !(kt & 1) && kt <= kPairEnd;
            const bool tree = kt == 0;
            const bool hand_over = wg == 0 || kt < kTiles - 1;
            if (!pv_only) {
                const uint64_t dk = make_desc(sb + kOffRing + r.s * kTileBytes, 2048);
                mbar_wait(bar_full + 8 * (r.s * kSub), r.ph);
                mbar_wait(bar_full + 8 * (r.s * kSub + 1), r.ph);
                wg_fence();
#pragma unroll
                for (int k = 0; k < 8; k++) {
                    const uint32_t off = ((k >> 2) * 1024 + (k & 3) * 32) >> 4;
                    wgmma_qk64<0>(sc, dq + off, dk + off, k != 0);
                }
                wg_commit();
                mbar_wait(bar_full + 8 * (r.s * kSub + 2), r.ph);
                mbar_wait(bar_full + 8 * (r.s * kSub + 3), r.ph);
                bar_sync(1 + wg);
                wg_fence();
#pragma unroll
                for (int k = 0; k < 8; k++) {
                    const uint32_t off = ((k >> 2) * 1024 + (k & 3) * 32) >> 4;
                    wgmma_qk64<32>(sc, dq + off, dk + (16384 >> 4) + off, k != 0);
                }
                wg_commit();
                if (hand_over) bar_arrive(2 - wg);
                wg_wait<1>();
                fence_regs<0, 32>(sc);
                float x0 = fmaxf(sc[0], sc[1]), x1 = fmaxf(sc[2], sc[3]);
#pragma unroll
                for (int i = 1; i < 8; i++) {
                    x0 = fmaxf(x0, fmaxf(sc[4 * i], sc[4 * i + 1]));
                    x1 = fmaxf(x1, fmaxf(sc[4 * i + 2], sc[4 * i + 3]));
                }
                asm volatile("" : "+f"(x0), "+f"(x1)::"memory");
                wg_wait<0>();
                fence_regs<32, 64>(sc);
                if (lane == 0) mbar_arrive(bar_empty + 8 * r.s);
                r.next();

#pragma unroll
                for (int i = 8; i < 16; i++) {
                    x0 = fmaxf(x0, fmaxf(sc[4 * i], sc[4 * i + 1]));
                    x1 = fmaxf(x1, fmaxf(sc[4 * i + 2], sc[4 * i + 3]));
                }
                float n0 = fmaxf(m0, quad_max(x0) * c), n1 = fmaxf(m1, quad_max(x1) * c);
                moved = __any_sync(0xffffffffu, n0 > m0 || n1 > m1);
                {
                    float z;
                    asm volatile("st.volatile.shared.f32 [%2 + 4], %3;\n"
                                 "barrier.sync %1, 256;\nld.volatile.shared.f32 %0, [%2];"
                                 : "=f"(z) : "r"(3 + wg), "r"(pace_slot + 12), "f"(n0 + n1) : "memory");
                    n0 += z;
                    n1 += z;
                }
                a0 = ex2(m0 - n0);
                a1 = ex2(m1 - n1);
                m0 = n0;
                m1 = n1;
                l0 *= a0;
                l1 *= a1;
#pragma unroll
                for (int i = 0; i < 16; i++) {
                    sc[4 * i] = ex2(fmaf(sc[4 * i], c, -n0));
                    sc[4 * i + 1] = ex2(fmaf(sc[4 * i + 1], c, -n0));
                    sc[4 * i + 2] = ex2(fmaf(sc[4 * i + 2], c, -n1));
                    sc[4 * i + 3] = ex2(fmaf(sc[4 * i + 3], c, -n1));
                    l0 += sc[4 * i] + sc[4 * i + 1];
                    l1 += sc[4 * i + 2] + sc[4 * i + 3];
                }
                {
                    asm volatile("st.volatile.shared.f32 [%0], %1;" ::"r"(pace_slot + 16), "f"(sc[59]) : "memory");
                    if (hand_over) bar_arrive(4 - wg);
                }
                if (++kt == kTiles) break;
            }

            if (pending) {
                const uint32_t vslot = sb + kOffRing + r.s * kTileBytes;
                const uint32_t vbar = bar_full + 8 * (r.s * kSub);
                if (!tree) mbar_wait(vbar, r.ph);
                pv_piece(o, p, tree ? sb + kOffVt : vslot);
                if (!tree) {
#pragma unroll
                    for (int u = 1; u < 4; u++) {
                        mbar_wait(vbar + 8 * u, r.ph);
                        pv_piece(o, p + 8 * u, vslot + u * kSubBytes);
                    }
                }
            }
            wg_wait<0>();
            fence_regs<0, 64>(o);
            if (pending && !tree) {
                if (lane == 0) mbar_arrive(bar_empty + 8 * r.s);
                r.next();
            }
            pending = !pv_only;
            if (!pv_only) {
                if (moved) {
#pragma unroll
                    for (int i = 0; i < 16; i++) {
                        o[4 * i] *= a0;
                        o[4 * i + 1] *= a0;
                        o[4 * i + 2] *= a1;
                        o[4 * i + 3] *= a1;
                    }
                }
#pragma unroll
                for (int i = 0; i < 16; i++) {
                    p[2 * i] = pack_bf16(sc[4 * i], sc[4 * i + 1]);
                    p[2 * i + 1] = pack_bf16(sc[4 * i + 2], sc[4 * i + 3]);
                }
            }
        }

#pragma unroll
        for (int h = 0; h < 2; h++) {
            const float a = h ? a1 : a0;
            if (__any_sync(0xffffffffu, a != 1.f)) {
                const uint32_t hi = pack_bf16(a, a);
                const float rest = a - __uint_as_float(hi << 16);
                const uint32_t lo = pack_bf16(rest, rest);
#pragma unroll
                for (int i = 0; i < 16; i++) {
                    o[4 * i + 2 * h] *= a;
                    o[4 * i + 2 * h + 1] *= a;
                    asm("{\n.reg .b32 t;\nmul.rn.bf16x2 t, %0, %2;\nfma.rn.bf16x2 %0, %0, %1, t;\n}" : "+r"(p[2 * i + h]) : "r"(hi), "r"(lo));
                }
            }
        }
        float i0, i1;
        const uint32_t stg = sb + kOffQ + warp * 4096;
        const uint32_t swz = ((lane >> 3) ^ (lane & 7)) << 4;
        uint32_t sa = stg + (lane & 7) * 128 + swz, sa2 = sa ^ 64;
        uint32_t la = stg + (lane >> 3) * 128 + swz, la2 = (la ^ 64) + 512;
        uint4* gp = reinterpret_cast<uint4*>(out + (size_t)(cta * kRows + warp * 16 + (lane >> 3)) * kD) + (lane & 7);
        asm volatile("" : "+r"(sa), "+r"(sa2), "+r"(la), "+r"(la2), "+l"(gp));
        uint4 vv[4] = {};
        auto put = [&](int j, int h) {
            asm volatile("st.global.v4.u32 [%0], {%1, %2, %3, %4};"
                         ::"l"(gp + 64 * j + 8 * h), "r"(vv[j].x), "r"(vv[j].y), "r"(vv[j].z), "r"(vv[j].w) : "memory");
        };
        auto store_half = [&](auto hc) {
            constexpr int h = decltype(hc)::value;
#pragma unroll
            for (int hr = 0; hr < 2; hr++) {
                const float f = hr ? i1 : i0;
#pragma unroll
                for (int i = 0; i < 2; i++) {
                    const float* v = o + 32 * h + 16 * i + 2 * hr;
                    asm volatile("stmatrix.sync.aligned.m8n8.x4.shared.b16 [%0], {%1, %2, %3, %4};"
                                 ::"r"((i ? sa2 : sa) + hr * 1024 + h * 2048), "r"(pack_bf16(v[0] * f, v[1] * f)),
                                   "r"(pack_bf16(v[4] * f, v[5] * f)), "r"(pack_bf16(v[8] * f, v[9] * f)),
                                   "r"(pack_bf16(v[12] * f, v[13] * f)) : "memory");
                }
                __syncwarp();
                uint4* v = vv + 2 * hr;
#pragma unroll
                for (int i = 0; i < 2; i++)
                    asm volatile("ld.volatile.shared.v4.u32 {%0, %1, %2, %3}, [%4];" : "=r"(v[i].x), "=r"(v[i].y), "=r"(v[i].z), "=r"(v[i].w)
                                 : "r"((i ? la2 : la) + hr * 1024 + h * 2048) : "memory");
                if (h || !hr) {
                    put(2 * hr, h);
                    put(2 * hr + 1, h);
                }
            }
        };
        auto pack_last = [&]() {
            i0 = rcp(quad_sum(l0));
            i1 = rcp(quad_sum(l1));
#pragma unroll
            for (int i = 0; i < 16; i++) {
                p[32 + 2 * i] = pack_bf16(sc[4 * i], sc[4 * i + 1]);
                p[32 + 2 * i + 1] = pack_bf16(sc[4 * i + 2], sc[4 * i + 3]);
            }
#pragma unroll
            for (int i = 32; i < 64; i++) asm volatile("" : "+r"(p[i])::"memory");
            asm volatile("" : "+f"(i0), "+f"(i1)::"memory");
        };
        const uint64_t dend = make_desc(sb + kOffRing + kEndSlot * kTileBytes, 1024);
        static_for<kEnd>([&](auto yc) {
            constexpr int y = yc.value;
            constexpr EndPiece e = end_piece(y);
            constexpr int step = e.kind == F ? 4096 : 2048;
            const uint64_t dv = dend + (end_offset(y) >> 4) + (e.kind == F ? (uint64_t)(1024 >> 4) << 32 : 0);
            mbar_wait(bar_end + 8 * y, 0);
            wg_fence();
            if (e.kind != R) {
#pragma unroll
                for (int k = 0; k < e.nk; k++) wgmma_pv64<0>(o, p + 4 * (e.k0 + k), dv + ((k * step) >> 4));
                wg_commit();
            }
            if (e.kind != L) {
#pragma unroll
                for (int k = 0; k < e.nk; k++) wgmma_pv64<32>(o, p + 4 * (e.k0 + k), dv + ((k * step + (e.kind == F ? 1024 : 0)) >> 4));
                wg_commit();
            }
            if (y == 0) pack_last();
            if (y == kEndLeft + 1) {
                put(2, 0);
                put(3, 0);
            }
            if (y == kEndLeft) {
                wg_wait<1>();
                fence_regs<0, 32>(o);
                store_half(IntC<0>{});
            }
        });
        wg_wait<0>();
        fence_regs<32, 64>(o);
        store_half(IntC<1>{});
    }
}

typedef CUresult (*EncodeFn)(CUtensorMap*, CUtensorMapDataType, cuuint32_t, void*, const cuuint64_t*,
                             const cuuint64_t*, const cuuint32_t*, const cuuint32_t*, CUtensorMapInterleave,
                             CUtensorMapSwizzle, CUtensorMapL2promotion, CUtensorMapFloatOOBfill);

void make_map(EncodeFn enc, CUtensorMap* m, const void* p, uint64_t rows, uint32_t box_rows, uint32_t halves) {
    const cuuint64_t dims[4] = {64, 8, 2, rows / 8};
    const cuuint64_t strides[3] = {256, 128, 2048};
    const cuuint32_t box[4] = {64, 8, halves, box_rows / 8};
    const cuuint32_t es[4] = {1, 1, 1, 1};
    enc(m, CU_TENSOR_MAP_DATA_TYPE_BFLOAT16, 4, const_cast<void*>(p), dims, strides, box, es,
        CU_TENSOR_MAP_INTERLEAVE_NONE, CU_TENSOR_MAP_SWIZZLE_128B,
        halves == 2 ? CU_TENSOR_MAP_L2_PROMOTION_L2_256B : CU_TENSOR_MAP_L2_PROMOTION_L2_128B,
        CU_TENSOR_MAP_FLOAT_OOB_FILL_NONE);
}

}

extern "C" void kernel_launch(void* const* d_in, const int* in_sizes, int n_in, void* d_out, int out_size) {
    (void)in_sizes; (void)n_in; (void)out_size;
    static EncodeFn enc = nullptr;
    static unsigned int* progress = nullptr;
    if (!enc) {
        cudaDriverEntryPointQueryResult qr;
        cudaGetDriverEntryPoint("cuTensorMapEncodeTiled", (void**)&enc, cudaEnableDefault, &qr);
        cudaFuncSetAttribute(tree_attn_kernel, cudaFuncAttributeMaxDynamicSharedMemorySize, kSmemBytes);
        cudaGetSymbolAddress((void**)&progress, g_progress);
    }
    Maps tm;
    make_map(enc, &tm.q, d_in[0], (uint64_t)kCtas * kRows, kRows, 2);
    make_map(enc, &tm.k, d_in[1], (uint64_t)kCtas * kC, 32, 2);
    make_map(enc, &tm.v, d_in[2], (uint64_t)kCtas * kC, 32, 2);
    make_map(enc, &tm.vh64, d_in[2], (uint64_t)kCtas * kC, 64, 1);
    make_map(enc, &tm.vh32, d_in[2], (uint64_t)kCtas * kC, 32, 1);
    make_map(enc, &tm.kt, d_in[3], (uint64_t)kCtas * kT, kT, 2);
    make_map(enc, &tm.vt, d_in[4], (uint64_t)kCtas * kT, kT, 2);
    tree_attn_kernel<<<kCtas, kThreads, kSmemBytes, cudaStreamPerThread>>>(
        (const __nv_bfloat16*)d_in[0], (const __nv_bfloat16*)d_in[5], (__nv_bfloat16*)d_out, progress, tm);
}
```
